```python
import torch

def _softmax(x, axis=-1):
    return torch.softmax(x, dim=axis)
def _gelu(x):
    return torch.nn.functional.gelu(x, approximate="tanh")
def _silu(x):
    return torch.nn.functional.silu(x)
def _sigmoid(x):
    return torch.sigmoid(x)
def _layernorm(x, axis=-1, eps=1e-5):
    m = x.mean(dim=axis, keepdim=True)
    v = x.var(dim=axis, keepdim=True, unbiased=False)
    return (x - m) / torch.sqrt(v + eps)
def _scatter_add(tgt, idx, src, axis=0):
    return tgt.clone().index_add_(axis, idx, src)
def _segment_sum(src, seg, n):
    out = torch.zeros((n,) + src.shape[1:], dtype=src.dtype)
    return out.index_add_(0, seg, src)
def _pad(x, pw):
    flat = tuple(v for pair in reversed(pw) for v in pair)
    return torch.nn.functional.pad(x, flat)

kernel_name = 'standalone__molecular_angular_gemnet__graph'

def setup_inputs():

    _w = (lambda a: (lambda t: t.to(torch.bfloat16) if t.is_floating_point() else t)(torch.as_tensor(a)))
    N, deg, De, L = 25000, 16, 16, 3
    E = N * deg
    T = E * deg
    NR = 8
    dist = torch.rand(E).to(float)
    angle = (torch.rand(T) * torch.pi).to(float)
    centers = torch.linspace(0.0, 1.0, NR).to(float)
    ang_freq = torch.arange(1, L + 1).to(float)
    return {
        "m": _w((lambda *s: torch.randn(*s, dtype=torch.bfloat16) * 0.05)(E, De)),
        "idx_in": _w((lambda lo, hi, *s: torch.randint(lo, hi, s))(0, E, T).to(torch.int64)),
        "idx_out": _w((lambda lo, hi, *s: torch.randint(lo, hi, s))(0, E, T).to(torch.int64)),
        "dist": _w(dist),
        "angle": _w(angle),
        "centers": _w(centers),
        "ang_freq": _w(ang_freq),
        "w_rbf": _w((lambda *s: torch.randn(*s, dtype=torch.bfloat16) * 0.2)(NR, De)),
        "w_sbf": _w((lambda *s: torch.randn(*s, dtype=torch.bfloat16) * 0.2)(NR * L, De)),
        "w_down": _w((lambda *s: torch.randn(*s, dtype=torch.bfloat16) * 0.2)(De, De)),
        "w_up": _w((lambda *s: torch.randn(*s, dtype=torch.bfloat16) * 0.2)(De, De)),
    }

def reference(m, idx_in, idx_out, dist, angle, centers, ang_freq, w_rbf, w_sbf, w_down, w_up):
    E, De = m.shape[0], m.shape[1]
    NR = centers.shape[0]
    L = ang_freq.shape[0]
    rbf = torch.exp(-10.0 * (dist[:, None] - centers[None, :]) ** 2)
    cbf = torch.cos(ang_freq[None, :] * angle[:, None])
    rbf_t = rbf[idx_out]
    sbf = torch.reshape(rbf_t[:, :, None] * cbf[:, None, :], (-1, NR * L))
    x = (m[idx_in] @ w_down) * (sbf @ w_sbf)
    agg = _segment_sum(x, idx_out, E)
    return m + (agg @ w_up) * (rbf @ w_rbf)
```

```cpp
#include <cuda_runtime.h>
#include <cuda_bf16.h>
#include <stdint.h>

namespace {

constexpr int kMaxE   = 400000;
constexpr int IDX_BITS = 19;
constexpr int EB_LOG  = 8;
constexpr int EB      = 1 << EB_LOG;
constexpr int NB_MAX  = (kMaxE + EB - 1) / EB;
constexpr int NB_PAD  = 2048;
constexpr int CAP     = 4608;

constexpr int P1_THREADS = 512;
constexpr int P1_RPT     = 16;
constexpr int C1         = P1_THREADS * P1_RPT;

constexpr int P2_THREADS = 512;
constexpr int P2_RPT     = CAP / P2_THREADS;

__device__ uint32_t g_cnt[NB_PAD];
__device__ uint32_t g_w[(size_t)NB_MAX * CAP];
__device__ uint16_t g_a[(size_t)NB_MAX * CAP];

__device__ __forceinline__ int4 ld_stream4(const int4* p) { return __ldcs(p); }
__device__ __forceinline__ uint2 ld_stream2(const uint2* p) { return __ldcs(p); }

__device__ __forceinline__ float bf16r(float x) { return __bfloat162float(__float2bfloat16_rn(x)); }
__device__ __forceinline__ float bf16_bits_to_f(uint32_t h) { return __uint_as_float(h << 16); }
__device__ __forceinline__ uint32_t pack_bf16(float lo, float hi) {
    __nv_bfloat162 v = __floats2bfloat162_rn(lo, hi);
    return *reinterpret_cast<uint32_t*>(&v);
}

__device__ __forceinline__ float cos_acc(float x) {
    if (fabsf(x) > 1000.f) return cosf(x);
    float k = rintf(x * 0.15915494309189535f);
    float r = fmaf(k, -6.28318548202514648f, x);
    r = fmaf(k, 1.7484555314695172e-7f, r);
    return __cosf(r);
}
__device__ __forceinline__ float cbf_val(float freq, float ang) {
    return bf16r(cos_acc(bf16r(freq * ang)));
}
__device__ __forceinline__ float rbf_val(float d, float c) {
    float x = bf16r(d - c);
    float s = bf16r(x * x);
    float a = bf16r(-10.f * s);
    return bf16r(expf(a));
}

__device__ __forceinline__ void mma16816(float* d, uint32_t a0, uint32_t a1, uint32_t a2, uint32_t a3,
                                         uint32_t b0, uint32_t b1) {
    asm volatile("mma.sync.aligned.m16n8k16.row.col.f32.bf16.bf16.f32 {%0,%1,%2,%3}, {%4,%5,%6,%7}, {%8,%9}, {%0,%1,%2,%3};"
                 : "+f"(d[0]), "+f"(d[1]), "+f"(d[2]), "+f"(d[3])
                 : "r"(a0), "r"(a1), "r"(a2), "r"(a3), "r"(b0), "r"(b1));
}
__device__ __forceinline__ void mma1688(float* d, uint32_t a0, uint32_t a1, uint32_t b0) {
    asm volatile("mma.sync.aligned.m16n8k8.row.col.f32.bf16.bf16.f32 {%0,%1,%2,%3}, {%4,%5}, {%6}, {%0,%1,%2,%3};"
                 : "+f"(d[0]), "+f"(d[1]), "+f"(d[2]), "+f"(d[3])
                 : "r"(a0), "r"(a1), "r"(b0));
}

__global__ void __launch_bounds__(P1_THREADS, 2)
part_kernel(const int* __restrict__ idx_in, const int* __restrict__ idx_out,
            const uint16_t* __restrict__ angle, int T)
{
    extern __shared__ __align__(16) uint2 stage[];
    __shared__ __align__(16) uint32_t s_off[NB_PAD];
    __shared__ __align__(16) int      s_delta[NB_PAD];
    __shared__ uint32_t s_warp[P1_THREADS / 32];

    const int tid = threadIdx.x;
    const int base = blockIdx.x * C1;

    int4 o[4], in[4];
    uint2 a[4];
#pragma unroll
    for (int j = 0; j < 4; j++) {
        int v = base / 4 + j * P1_THREADS + tid;
        if (v * 4 < T) {
            o[j]  = ld_stream4(reinterpret_cast<const int4*>(idx_out) + v);
            in[j] = ld_stream4(reinterpret_cast<const int4*>(idx_in) + v);
            a[j]  = ld_stream2(reinterpret_cast<const uint2*>(angle) + v);
        } else {
            o[j] = make_int4(-1, -1, -1, -1); in[j] = make_int4(0, 0, 0, 0); a[j] = make_uint2(0, 0);
        }
    }
    reinterpret_cast<uint4*>(s_off)[tid] = make_uint4(0, 0, 0, 0);
    __syncthreads();

    uint32_t rk[16];
#pragma unroll
    for (int j = 0; j < 4; j++) {
        const int ov[4] = {o[j].x, o[j].y, o[j].z, o[j].w};
#pragma unroll
        for (int k = 0; k < 4; k++)
            rk[j * 4 + k] = (ov[k] >= 0) ? atomicAdd(&s_off[ov[k] >> EB_LOG], 1u) : 0u;
    }
    __syncthreads();

    uint4 c = reinterpret_cast<uint4*>(s_off)[tid];
    uint32_t sum = c.x + c.y + c.z + c.w;
    uint32_t inc = sum;
#pragma unroll
    for (int d = 1; d < 32; d <<= 1) {
        uint32_t t = __shfl_up_sync(0xffffffffu, inc, d);
        if ((tid & 31) >= d) inc += t;
    }
    if ((tid & 31) == 31) s_warp[tid >> 5] = inc;
    uint32_t g0 = c.x ? atomicAdd(&g_cnt[4 * tid + 0], c.x) : 0u;
    uint32_t g1 = c.y ? atomicAdd(&g_cnt[4 * tid + 1], c.y) : 0u;
    uint32_t g2 = c.z ? atomicAdd(&g_cnt[4 * tid + 2], c.z) : 0u;
    uint32_t g3 = c.w ? atomicAdd(&g_cnt[4 * tid + 3], c.w) : 0u;
    __syncthreads();
    uint32_t wpre = 0;
#pragma unroll
    for (int w = 0; w < P1_THREADS / 32; w++) wpre += (w < (tid >> 5)) ? s_warp[w] : 0u;
    uint32_t ex = wpre + inc - sum;
    uint4 off = make_uint4(ex, ex + c.x, ex + c.x + c.y, ex + c.x + c.y + c.z);
    reinterpret_cast<uint4*>(s_off)[tid] = off;
    __syncthreads();

#pragma unroll
    for (int j = 0; j < 4; j++) {
        const int ov[4] = {o[j].x, o[j].y, o[j].z, o[j].w};
        const int iv[4] = {in[j].x, in[j].y, in[j].z, in[j].w};
        const uint32_t av[4] = {a[j].x & 0xffffu, a[j].x >> 16, a[j].y & 0xffffu, a[j].y >> 16};
#pragma unroll
        for (int k = 0; k < 4; k++) {
            if (ov[k] >= 0) {
                uint32_t b = (uint32_t)ov[k] >> EB_LOG;
                uint32_t p = s_off[b] + rk[j * 4 + k];
                stage[p] = make_uint2((uint32_t)iv[k] | ((uint32_t)(ov[k] & (EB - 1)) << IDX_BITS),
                                      av[k] | (b << 16));
            }
        }
    }
    reinterpret_cast<int4*>(s_delta)[tid] =
        make_int4((int)(g0 - off.x), (int)(g1 - off.y), (int)(g2 - off.z), (int)(g3 - off.w));
    __syncthreads();

    const int n = min(C1, T - base);
#pragma unroll 4
    for (int i = tid; i < n; i += P1_THREADS) {
        uint2 r = stage[i];
        uint32_t b = r.y >> 16;
        uint32_t p = (uint32_t)(i + s_delta[b]);
        if (p < (uint32_t)CAP) {
            g_w[(size_t)b * CAP + p] = r.x;
            g_a[(size_t)b * CAP + p] = (uint16_t)r.y;
        }
    }
}

__global__ void __launch_bounds__(P2_THREADS, 2)
edge_kernel(const uint16_t* __restrict__ m, const int* __restrict__ idx_in, const int* __restrict__ idx_out,
            const uint16_t* __restrict__ dist, const uint16_t* __restrict__ angle,
            const uint16_t* __restrict__ centers, const uint16_t* __restrict__ ang_freq,
            const uint16_t* __restrict__ w_rbf, const uint16_t* __restrict__ w_sbf,
            const uint16_t* __restrict__ w_down, const uint16_t* __restrict__ w_up,
            uint16_t* __restrict__ out, int E, int T)
{
    extern __shared__ __align__(16) uint4 srec[];
    __shared__ uint32_t s_start[EB + 1];
    __shared__ uint32_t s_wsum[EB / 32];
    __shared__ uint32_t s_n;

    const int tid  = threadIdx.x;
    const int lane = tid & 31;
    const int warp = tid >> 5;
    const int g    = lane >> 2;
    const int t    = lane & 3;
    const int b    = blockIdx.x;

    if (tid == 0) { s_n = g_cnt[b]; g_cnt[b] = 0; }
    if (tid < EB) s_start[tid] = 0;
    const float f0 = bf16_bits_to_f(ang_freq[0]);
    const float f1 = bf16_bits_to_f(ang_freq[1]);
    const float f2 = bf16_bits_to_f(ang_freq[2]);
    __syncthreads();
    const uint32_t n = s_n;

    float S[2][3][4];
#pragma unroll
    for (int h = 0; h < 2; h++)
#pragma unroll
        for (int l = 0; l < 3; l++)
#pragma unroll
            for (int j = 0; j < 4; j++) S[h][l][j] = 0.f;

    if (n <= (uint32_t)CAP) {
        uint32_t w[P2_RPT], av[P2_RPT], rk[P2_RPT];
        const uint32_t* gw = g_w + (size_t)b * CAP;
        const uint16_t* ga = g_a + (size_t)b * CAP;
#pragma unroll
        for (int k = 0; k < P2_RPT; k++) {
            uint32_t i = tid + k * P2_THREADS;
            if (i < n) { w[k] = __ldcs(gw + i); av[k] = __ldcs(ga + i); }
        }
#pragma unroll
        for (int k = 0; k < P2_RPT; k++) {
            uint32_t i = tid + k * P2_THREADS;
            if (i < n) rk[k] = atomicAdd(&s_start[w[k] >> IDX_BITS], 1u);
        }
        __syncthreads();
        uint32_t cnt = 0, inc = 0;
        if (tid < EB) {
            cnt = s_start[tid];
            inc = cnt;
#pragma unroll
            for (int d = 1; d < 32; d <<= 1) {
                uint32_t x = __shfl_up_sync(0xffffffffu, inc, d);
                if (lane >= d) inc += x;
            }
            if (lane == 31) s_wsum[warp] = inc;
        }
        __syncthreads();
        if (tid < EB) {
            uint32_t pre = 0;
#pragma unroll
            for (int x = 0; x < EB / 32; x++) pre += (x < warp) ? s_wsum[x] : 0u;
            s_start[tid] = pre + inc - cnt;
            if (tid == EB - 1) s_start[EB] = pre + inc;
        }
        __syncthreads();
#pragma unroll
        for (int k = 0; k < P2_RPT; k++) {
            uint32_t i = tid + k * P2_THREADS;
            if (i < n) {
                uint32_t p = s_start[w[k] >> IDX_BITS] + rk[k];
                float an = bf16_bits_to_f(av[k]);
                srec[p] = make_uint4((w[k] & ((1u << IDX_BITS) - 1)) * 32u,
                                     __float_as_uint(cbf_val(f0, an)),
                                     __float_as_uint(cbf_val(f1, an)),
                                     __float_as_uint(cbf_val(f2, an)));
            }
        }
        __syncthreads();

        const char* mbase = reinterpret_cast<const char*>(m) + t * 8;
#pragma unroll
        for (int h = 0; h < 2; h++) {
            const int el = 16 * warp + 8 * h + g;
            const uint32_t s = s_start[el], en = s_start[el + 1];
            for (uint32_t i = s; i < en; i += 4) {
                uint4 r[4]; uint2 v[4];
#pragma unroll
                for (int u = 0; u < 4; u++) {
                    if (i + u < en) {
                        r[u] = srec[i + u];
                        v[u] = __ldg(reinterpret_cast<const uint2*>(mbase + r[u].x));
                    } else {
                        r[u] = make_uint4(0, 0, 0, 0); v[u] = make_uint2(0, 0);
                    }
                }
#pragma unroll
                for (int u = 0; u < 4; u++) {
                    float x0 = __uint_as_float(v[u].x << 16), x1 = __uint_as_float(v[u].x & 0xffff0000u);
                    float x2 = __uint_as_float(v[u].y << 16), x3 = __uint_as_float(v[u].y & 0xffff0000u);
                    float c0 = __uint_as_float(r[u].y), c1 = __uint_as_float(r[u].z), c2 = __uint_as_float(r[u].w);
                    S[h][0][0] = fmaf(c0, x0, S[h][0][0]); S[h][0][1] = fmaf(c0, x1, S[h][0][1]);
                    S[h][0][2] = fmaf(c0, x2, S[h][0][2]); S[h][0][3] = fmaf(c0, x3, S[h][0][3]);
                    S[h][1][0] = fmaf(c1, x0, S[h][1][0]); S[h][1][1] = fmaf(c1, x1, S[h][1][1]);
                    S[h][1][2] = fmaf(c1, x2, S[h][1][2]); S[h][1][3] = fmaf(c1, x3, S[h][1][3]);
                    S[h][2][0] = fmaf(c2, x0, S[h][2][0]); S[h][2][1] = fmaf(c2, x1, S[h][2][1]);
                    S[h][2][2] = fmaf(c2, x2, S[h][2][2]); S[h][2][3] = fmaf(c2, x3, S[h][2][3]);
                }
            }
        }
    } else {
        float* sacc = reinterpret_cast<float*>(srec);
        for (int i = tid; i < EB * 48; i += P2_THREADS) sacc[i] = 0.f;
        __syncthreads();
        for (int i = tid; i < T; i += P2_THREADS) {
            int o = idx_out[i];
            if ((o >> EB_LOG) == b) {
                float an = bf16_bits_to_f(angle[i]);
                float c[3] = {cbf_val(f0, an), cbf_val(f1, an), cbf_val(f2, an)};
                const uint16_t* row = m + (size_t)idx_in[i] * 16;
                float* dst = sacc + (o & (EB - 1)) * 48;
                for (int k = 0; k < 16; k++) {
                    float x = bf16_bits_to_f(row[k]);
                    atomicAdd(dst + k, c[0] * x);
                    atomicAdd(dst + 16 + k, c[1] * x);
                    atomicAdd(dst + 32 + k, c[2] * x);
                }
            }
        }
        __syncthreads();
#pragma unroll
        for (int h = 0; h < 2; h++) {
            const int el = 16 * warp + 8 * h + g;
#pragma unroll
            for (int l = 0; l < 3; l++)
#pragma unroll
                for (int j = 0; j < 4; j++) S[h][l][j] = sacc[el * 48 + l * 16 + 4 * t + j];
        }
    }

    const int eA = b * EB + 16 * warp + g;
    const int eB = eA + 8;
    const bool okA = eA < E, okB = eB < E;

    const float cA = bf16_bits_to_f(centers[2 * t]), cB = bf16_bits_to_f(centers[2 * t + 1]);
    const float dA = okA ? bf16_bits_to_f(dist[eA]) : 0.f;
    const float dB = okB ? bf16_bits_to_f(dist[eB]) : 0.f;
    const uint32_t ra0 = pack_bf16(rbf_val(dA, cA), rbf_val(dA, cB));
    const uint32_t ra1 = pack_bf16(rbf_val(dB, cA), rbf_val(dB, cB));

    auto ld2 = [](const uint16_t* p0, const uint16_t* p1) -> uint32_t {
        return (uint32_t)__ldg(p0) | ((uint32_t)__ldg(p1) << 16);
    };

    float y[3][2][4];
#pragma unroll
    for (int tl = 0; tl < 3; tl++)
#pragma unroll
        for (int j = 0; j < 2; j++)
#pragma unroll
            for (int i = 0; i < 4; i++) y[tl][j][i] = 0.f;
    {
        uint32_t wd[2][2];
#pragma unroll
        for (int j = 0; j < 2; j++) {
            wd[j][0] = ld2(w_down + (4 * t + 0) * 16 + 8 * j + g, w_down + (4 * t + 1) * 16 + 8 * j + g);
            wd[j][1] = ld2(w_down + (4 * t + 2) * 16 + 8 * j + g, w_down + (4 * t + 3) * 16 + 8 * j + g);
        }
#pragma unroll
        for (int tl = 0; tl < 3; tl++) {
            const float* P = (tl == 0) ? S[0][0] : (tl == 1) ? S[1][0] : S[0][2];
            const float* Q = (tl == 0) ? S[0][1] : (tl == 1) ? S[1][1] : S[1][2];
            uint32_t h0 = pack_bf16(P[0], P[1]), h1 = pack_bf16(Q[0], Q[1]);
            uint32_t h2 = pack_bf16(P[2], P[3]), h3 = pack_bf16(Q[2], Q[3]);
            uint32_t l0 = pack_bf16(P[0] - __uint_as_float(h0 << 16), P[1] - __uint_as_float(h0 & 0xffff0000u));
            uint32_t l1 = pack_bf16(Q[0] - __uint_as_float(h1 << 16), Q[1] - __uint_as_float(h1 & 0xffff0000u));
            uint32_t l2 = pack_bf16(P[2] - __uint_as_float(h2 << 16), P[3] - __uint_as_float(h2 & 0xffff0000u));
            uint32_t l3 = pack_bf16(Q[2] - __uint_as_float(h3 << 16), Q[3] - __uint_as_float(h3 & 0xffff0000u));
#pragma unroll
            for (int j = 0; j < 2; j++) {
                mma16816(y[tl][j], h0, h1, h2, h3, wd[j][0], wd[j][1]);
                mma16816(y[tl][j], l0, l1, l2, l3, wd[j][0], wd[j][1]);
            }
        }
    }
    float aggA[2][2] = {{0.f, 0.f}, {0.f, 0.f}}, aggB[2][2] = {{0.f, 0.f}, {0.f, 0.f}};
#pragma unroll
    for (int l = 0; l < 3; l++) {
#pragma unroll
        for (int j = 0; j < 2; j++) {
            uint32_t ws = ld2(w_sbf + (3 * (2 * t) + l) * 16 + 8 * j + g, w_sbf + (3 * (2 * t + 1) + l) * 16 + 8 * j + g);
            float G[4] = {0.f, 0.f, 0.f, 0.f};
            mma1688(G, ra0, ra1, ws);
            float ya0, ya1, yb0, yb1;
            if (l == 0)      { ya0 = y[0][j][0]; ya1 = y[0][j][1]; yb0 = y[1][j][0]; yb1 = y[1][j][1]; }
            else if (l == 1) { ya0 = y[0][j][2]; ya1 = y[0][j][3]; yb0 = y[1][j][2]; yb1 = y[1][j][3]; }
            else             { ya0 = y[2][j][0]; ya1 = y[2][j][1]; yb0 = y[2][j][2]; yb1 = y[2][j][3]; }
            aggA[j][0] = fmaf(ya0, G[0], aggA[j][0]); aggA[j][1] = fmaf(ya1, G[1], aggA[j][1]);
            aggB[j][0] = fmaf(yb0, G[2], aggB[j][0]); aggB[j][1] = fmaf(yb1, G[3], aggB[j][1]);
        }
    }
    float u[2][4], rw[2][4];
    {
        uint32_t h0 = pack_bf16(aggA[0][0], aggA[0][1]), h1 = pack_bf16(aggB[0][0], aggB[0][1]);
        uint32_t h2 = pack_bf16(aggA[1][0], aggA[1][1]), h3 = pack_bf16(aggB[1][0], aggB[1][1]);
        uint32_t l0 = pack_bf16(aggA[0][0] - __uint_as_float(h0 << 16), aggA[0][1] - __uint_as_float(h0 & 0xffff0000u));
        uint32_t l1 = pack_bf16(aggB[0][0] - __uint_as_float(h1 << 16), aggB[0][1] - __uint_as_float(h1 & 0xffff0000u));
        uint32_t l2 = pack_bf16(aggA[1][0] - __uint_as_float(h2 << 16), aggA[1][1] - __uint_as_float(h2 & 0xffff0000u));
        uint32_t l3 = pack_bf16(aggB[1][0] - __uint_as_float(h3 << 16), aggB[1][1] - __uint_as_float(h3 & 0xffff0000u));
#pragma unroll
        for (int j = 0; j < 2; j++) {
            const int col = 4 * (g >> 1) + 2 * j + (g & 1);
            uint32_t b0 = ld2(w_up + (2 * t) * 16 + col, w_up + (2 * t + 1) * 16 + col);
            uint32_t b1 = ld2(w_up + (2 * t + 8) * 16 + col, w_up + (2 * t + 9) * 16 + col);
            uint32_t br = ld2(w_rbf + (2 * t) * 16 + col, w_rbf + (2 * t + 1) * 16 + col);
#pragma unroll
            for (int i = 0; i < 4; i++) { u[j][i] = 0.f; rw[j][i] = 0.f; }
            mma16816(u[j], h0, h1, h2, h3, b0, b1);
            mma16816(u[j], l0, l1, l2, l3, b0, b1);
            mma1688(rw[j], ra0, ra1, br);
        }
    }
    if (okA) {
        uint2 mv = __ldg(reinterpret_cast<const uint2*>(m + (size_t)eA * 16 + 4 * t));
        float o0 = fmaf(u[0][0], rw[0][0], __uint_as_float(mv.x << 16));
        float o1 = fmaf(u[0][1], rw[0][1], __uint_as_float(mv.x & 0xffff0000u));
        float o2 = fmaf(u[1][0], rw[1][0], __uint_as_float(mv.y << 16));
        float o3 = fmaf(u[1][1], rw[1][1], __uint_as_float(mv.y & 0xffff0000u));
        *reinterpret_cast<uint2*>(out + (size_t)eA * 16 + 4 * t) = make_uint2(pack_bf16(o0, o1), pack_bf16(o2, o3));
    }
    if (okB) {
        uint2 mv = __ldg(reinterpret_cast<const uint2*>(m + (size_t)eB * 16 + 4 * t));
        float o0 = fmaf(u[0][2], rw[0][2], __uint_as_float(mv.x << 16));
        float o1 = fmaf(u[0][3], rw[0][3], __uint_as_float(mv.x & 0xffff0000u));
        float o2 = fmaf(u[1][2], rw[1][2], __uint_as_float(mv.y << 16));
        float o3 = fmaf(u[1][3], rw[1][3], __uint_as_float(mv.y & 0xffff0000u));
        *reinterpret_cast<uint2*>(out + (size_t)eB * 16 + 4 * t) = make_uint2(pack_bf16(o0, o1), pack_bf16(o2, o3));
    }
}

}

extern "C" void kernel_launch(void* const* d_in, const int* in_sizes, int n_in,
                              void* d_out, int out_size) {
    const uint16_t* m        = (const uint16_t*)d_in[0];
    const int*      idx_in   = (const int*)d_in[1];
    const int*      idx_out  = (const int*)d_in[2];
    const uint16_t* dist     = (const uint16_t*)d_in[3];
    const uint16_t* angle    = (const uint16_t*)d_in[4];
    const uint16_t* centers  = (const uint16_t*)d_in[5];
    const uint16_t* ang_freq = (const uint16_t*)d_in[6];
    const uint16_t* w_rbf    = (const uint16_t*)d_in[7];
    const uint16_t* w_sbf    = (const uint16_t*)d_in[8];
    const uint16_t* w_down   = (const uint16_t*)d_in[9];
    const uint16_t* w_up     = (const uint16_t*)d_in[10];
    uint16_t* out = (uint16_t*)d_out;
    const int E = in_sizes[3];
    const int T = in_sizes[1];

    static bool init = false;
    if (!init) {
        cudaFuncSetAttribute(part_kernel, cudaFuncAttributeMaxDynamicSharedMemorySize, C1 * 8);
        cudaFuncSetAttribute(edge_kernel, cudaFuncAttributeMaxDynamicSharedMemorySize, CAP * 16);
        init = true;
    }
    const int nb = (E + EB - 1) / EB;
    part_kernel<<<(T + C1 - 1) / C1, P1_THREADS, C1 * 8>>>(idx_in, idx_out, angle, T);
    edge_kernel<<<nb, P2_THREADS, CAP * 16>>>(m, idx_in, idx_out, dist, angle, centers, ang_freq,
                                              w_rbf, w_sbf, w_down, w_up, out, E, T);
}
```

```cpp
#include <cuda_runtime.h>
#include <cuda_bf16.h>
#include <stdint.h>

namespace {

constexpr int kMaxE   = 400000;
constexpr int IDX_BITS = 19;
constexpr int EB_LOG  = 8;
constexpr int EB      = 1 << EB_LOG;
constexpr int NB_MAX  = (kMaxE + EB - 1) / EB;
constexpr int NB_PAD  = 2048;
constexpr int CAP     = 4608;
constexpr int CAPR    = 6144;
constexpr int STAGE_CAP = 11264;

constexpr int P1_THREADS = 512;
constexpr int P1_RPT     = 16;
constexpr int C1         = P1_THREADS * P1_RPT;

constexpr int P2_THREADS = 512;
constexpr int P2_RPT     = CAPR / P2_THREADS;

__device__ uint32_t g_cnt[NB_PAD];
__device__ __align__(128) uint2 g_q[(size_t)NB_MAX * CAPR];

__device__ __forceinline__ int4 ld_stream4(const int4* p) { return __ldcs(p); }
__device__ __forceinline__ uint2 ld_stream2(const uint2* p) { return __ldcs(p); }

__device__ __forceinline__ float bf16r(float x) { return __bfloat162float(__float2bfloat16_rn(x)); }
__device__ __forceinline__ float bf16_bits_to_f(uint32_t h) { return __uint_as_float(h << 16); }
__device__ __forceinline__ uint32_t pack_bf16(float lo, float hi) {
    __nv_bfloat162 v = __floats2bfloat162_rn(lo, hi);
    return *reinterpret_cast<uint32_t*>(&v);
}

__device__ __noinline__ float cos_slow(float x) { return cosf(x); }
__device__ __forceinline__ float cos_acc(float x) {
    if (fabsf(x) > 1000.f) return cos_slow(x);
    float k = rintf(x * 0.15915494309189535f);
    float r = fmaf(k, -6.28318548202514648f, x);
    r = fmaf(k, 1.7484555314695172e-7f, r);
    return __cosf(r);
}
__device__ __forceinline__ float cbf_val(float freq, float ang) {
    return bf16r(cos_acc(bf16r(freq * ang)));
}
__device__ __forceinline__ float rbf_val(float d, float c) {
    float x = bf16r(d - c);
    float s = bf16r(x * x);
    float a = bf16r(-10.f * s);
    return bf16r(expf(a));
}

__device__ __forceinline__ void mma16816(float* d, uint32_t a0, uint32_t a1, uint32_t a2, uint32_t a3,
                                         uint32_t b0, uint32_t b1) {
    asm volatile("mma.sync.aligned.m16n8k16.row.col.f32.bf16.bf16.f32 {%0,%1,%2,%3}, {%4,%5,%6,%7}, {%8,%9}, {%0,%1,%2,%3};"
                 : "+f"(d[0]), "+f"(d[1]), "+f"(d[2]), "+f"(d[3])
                 : "r"(a0), "r"(a1), "r"(a2), "r"(a3), "r"(b0), "r"(b1));
}
__device__ __forceinline__ void mma1688(float* d, uint32_t a0, uint32_t a1, uint32_t b0) {
    asm volatile("mma.sync.aligned.m16n8k8.row.col.f32.bf16.bf16.f32 {%0,%1,%2,%3}, {%4,%5}, {%6}, {%0,%1,%2,%3};"
                 : "+f"(d[0]), "+f"(d[1]), "+f"(d[2]), "+f"(d[3])
                 : "r"(a0), "r"(a1), "r"(b0));
}

__global__ void __launch_bounds__(P1_THREADS, 2)
part_kernel(const int* __restrict__ idx_in, const int* __restrict__ idx_out,
            const uint16_t* __restrict__ angle, int T)
{
    extern __shared__ __align__(16) uint2 stage[];
    __shared__ __align__(16) uint32_t s_off[NB_PAD];
    __shared__ __align__(16) int      s_delta[NB_PAD];
    __shared__ uint32_t s_warp[P1_THREADS / 32];

    const int tid = threadIdx.x;
    const int base = blockIdx.x * C1;

    int4 o[4], in[4];
    uint2 a[4];
#pragma unroll
    for (int j = 0; j < 4; j++) {
        int v = base / 4 + j * P1_THREADS + tid;
        if (v * 4 < T) {
            o[j]  = ld_stream4(reinterpret_cast<const int4*>(idx_out) + v);
            in[j] = ld_stream4(reinterpret_cast<const int4*>(idx_in) + v);
            a[j]  = ld_stream2(reinterpret_cast<const uint2*>(angle) + v);
        } else {
            o[j] = make_int4(-1, -1, -1, -1); in[j] = make_int4(0, 0, 0, 0); a[j] = make_uint2(0, 0);
        }
    }
    reinterpret_cast<uint4*>(s_off)[tid] = make_uint4(0, 0, 0, 0);
    __syncthreads();

    uint32_t rk[16];
#pragma unroll
    for (int j = 0; j < 4; j++) {
        const int ov[4] = {o[j].x, o[j].y, o[j].z, o[j].w};
#pragma unroll
        for (int k = 0; k < 4; k++)
            rk[j * 4 + k] = (ov[k] >= 0) ? atomicAdd(&s_off[ov[k] >> EB_LOG], 1u) : 0u;
    }
    __syncthreads();

    const uint4 c = reinterpret_cast<uint4*>(s_off)[tid];
    const uint4 cp = make_uint4((c.x + 3u) & ~3u, (c.y + 3u) & ~3u, (c.z + 3u) & ~3u, (c.w + 3u) & ~3u);
    uint32_t sum = cp.x + cp.y + cp.z + cp.w;
    uint32_t inc = sum;
#pragma unroll
    for (int d = 1; d < 32; d <<= 1) {
        uint32_t t = __shfl_up_sync(0xffffffffu, inc, d);
        if ((tid & 31) >= d) inc += t;
    }
    if ((tid & 31) == 31) s_warp[tid >> 5] = inc;
    uint32_t g0 = cp.x ? atomicAdd(&g_cnt[4 * tid + 0], cp.x) : 0u;
    uint32_t g1 = cp.y ? atomicAdd(&g_cnt[4 * tid + 1], cp.y) : 0u;
    uint32_t g2 = cp.z ? atomicAdd(&g_cnt[4 * tid + 2], cp.z) : 0u;
    uint32_t g3 = cp.w ? atomicAdd(&g_cnt[4 * tid + 3], cp.w) : 0u;
    __syncthreads();
    uint32_t wpre = 0, total = 0;
#pragma unroll
    for (int w = 0; w < P1_THREADS / 32; w++) { uint32_t x = s_warp[w]; wpre += (w < (tid >> 5)) ? x : 0u; total += x; }
    uint32_t ex = wpre + inc - sum;
    const uint4 off = make_uint4(ex, ex + cp.x, ex + cp.x + cp.y, ex + cp.x + cp.y + cp.z);
    reinterpret_cast<uint4*>(s_off)[tid] = off;
    reinterpret_cast<int4*>(s_delta)[tid] =
        make_int4((int)(g0 - off.x), (int)(g1 - off.y), (int)(g2 - off.z), (int)(g3 - off.w));
    {
        const uint32_t cc[4] = {c.x, c.y, c.z, c.w}, pp[4] = {cp.x, cp.y, cp.z, cp.w};
        const uint32_t oo[4] = {off.x, off.y, off.z, off.w}, gg[4] = {g0, g1, g2, g3};
#pragma unroll
        for (int k = 0; k < 4; k++) {
            for (uint32_t r = cc[k]; r < pp[k]; r++) {
                uint2 d = make_uint2(0xffffffffu, (uint32_t)(4 * tid + k) << 16);
                if (oo[k] + r < (uint32_t)STAGE_CAP) stage[oo[k] + r] = d;
                else if (gg[k] + r < (uint32_t)CAPR) g_q[(size_t)(4 * tid + k) * CAPR + gg[k] + r] = d;
            }
        }
    }
    __syncthreads();

#pragma unroll
    for (int j = 0; j < 4; j++) {
        const int ov[4] = {o[j].x, o[j].y, o[j].z, o[j].w};
        const int iv[4] = {in[j].x, in[j].y, in[j].z, in[j].w};
        const uint32_t av[4] = {a[j].x & 0xffffu, a[j].x >> 16, a[j].y & 0xffffu, a[j].y >> 16};
#pragma unroll
        for (int k = 0; k < 4; k++) {
            if (ov[k] >= 0) {
                uint32_t b = (uint32_t)ov[k] >> EB_LOG;
                uint32_t p = s_off[b] + rk[j * 4 + k];
                uint2 r = make_uint2((uint32_t)iv[k] | ((uint32_t)(ov[k] & (EB - 1)) << IDX_BITS),
                                     av[k] | (b << 16));
                if (p < (uint32_t)STAGE_CAP) stage[p] = r;
                else {
                    uint32_t gp = p + s_delta[b];
                    if (gp < (uint32_t)CAPR) g_q[(size_t)b * CAPR + gp] = r;
                }
            }
        }
    }
    __syncthreads();

    const int n = min((int)total, STAGE_CAP);
#pragma unroll 4
    for (int i = tid; i < n; i += P1_THREADS) {
        uint2 r = stage[i];
        uint32_t b = r.y >> 16;
        uint32_t p = (uint32_t)(i + s_delta[b]);
        if (p < (uint32_t)CAPR) g_q[(size_t)b * CAPR + p] = r;
    }
}

__global__ void __launch_bounds__(P2_THREADS, 2)
edge_kernel(const uint16_t* __restrict__ m, const int* __restrict__ idx_in, const int* __restrict__ idx_out,
            const uint16_t* __restrict__ dist, const uint16_t* __restrict__ angle,
            const uint16_t* __restrict__ centers, const uint16_t* __restrict__ ang_freq,
            const uint16_t* __restrict__ w_rbf, const uint16_t* __restrict__ w_sbf,
            const uint16_t* __restrict__ w_down, const uint16_t* __restrict__ w_up,
            uint16_t* __restrict__ out, int E, int T)
{
    extern __shared__ __align__(16) uint4 srec[];
    __shared__ uint32_t s_start[EB + 1];
    __shared__ uint32_t s_wsum[EB / 32];
    __shared__ uint32_t s_n;

    const int tid  = threadIdx.x;
    const int lane = tid & 31;
    const int warp = tid >> 5;
    const int g    = lane >> 2;
    const int t    = lane & 3;
    const int b    = blockIdx.x;

    if (tid == 0) { s_n = g_cnt[b]; g_cnt[b] = 0; }
    if (tid < EB) s_start[tid] = 0;
    const float f0 = bf16_bits_to_f(ang_freq[0]);
    const float f1 = bf16_bits_to_f(ang_freq[1]);
    const float f2 = bf16_bits_to_f(ang_freq[2]);
    __syncthreads();
    const uint32_t n = s_n;

    float S[2][3][4];
#pragma unroll
    for (int h = 0; h < 2; h++)
#pragma unroll
        for (int l = 0; l < 3; l++)
#pragma unroll
            for (int j = 0; j < 4; j++) S[h][l][j] = 0.f;

    bool fast = n <= (uint32_t)CAPR;
    uint32_t w[P2_RPT], av[P2_RPT], rk[P2_RPT];
    if (fast) {
        const uint4* gq = reinterpret_cast<const uint4*>(g_q + (size_t)b * CAPR);
#pragma unroll
        for (int k = 0; k < P2_RPT / 2; k++) {
            uint32_t i = tid + k * P2_THREADS;
            uint4 v = make_uint4(0xffffffffu, 0, 0xffffffffu, 0);
            if (2 * i < n) v = __ldcs(gq + i);
            w[2 * k] = v.x; av[2 * k] = v.y & 0xffffu; w[2 * k + 1] = v.z; av[2 * k + 1] = v.w & 0xffffu;
        }
#pragma unroll
        for (int k = 0; k < P2_RPT; k++)
            if (w[k] != 0xffffffffu) rk[k] = atomicAdd(&s_start[w[k] >> IDX_BITS], 1u);
        __syncthreads();
        uint32_t cnt = 0, inc = 0;
        if (tid < EB) {
            cnt = s_start[tid];
            inc = cnt;
#pragma unroll
            for (int d = 1; d < 32; d <<= 1) {
                uint32_t x = __shfl_up_sync(0xffffffffu, inc, d);
                if (lane >= d) inc += x;
            }
            if (lane == 31) s_wsum[warp] = inc;
        }
        __syncthreads();
        if (tid < EB) {
            uint32_t pre = 0;
#pragma unroll
            for (int x = 0; x < EB / 32; x++) pre += (x < warp) ? s_wsum[x] : 0u;
            s_start[tid] = pre + inc - cnt;
            if (tid == EB - 1) s_start[EB] = pre + inc;
        }
        __syncthreads();
        fast = s_start[EB] <= (uint32_t)CAP;
    }
    if (fast) {
#pragma unroll
        for (int k = 0; k < P2_RPT; k++) {
            if (w[k] != 0xffffffffu) {
                uint32_t p = s_start[w[k] >> IDX_BITS] + rk[k];
                float an = bf16_bits_to_f(av[k]);
                srec[p] = make_uint4((w[k] & ((1u << IDX_BITS) - 1)) * 32u,
                                     __float_as_uint(cbf_val(f0, an)),
                                     __float_as_uint(cbf_val(f1, an)),
                                     __float_as_uint(cbf_val(f2, an)));
            }
        }
        __syncthreads();

        const char* mbase = reinterpret_cast<const char*>(m) + t * 8;
#pragma unroll
        for (int h = 0; h < 2; h++) {
            const int el = 16 * warp + 8 * h + g;
            const uint32_t s = s_start[el], en = s_start[el + 1];
            for (uint32_t i = s; i < en; i += 4) {
                uint4 r[4]; uint2 v[4];
#pragma unroll
                for (int u = 0; u < 4; u++) {
                    if (i + u < en) {
                        r[u] = srec[i + u];
                        v[u] = __ldg(reinterpret_cast<const uint2*>(mbase + r[u].x));
                    } else {
                        r[u] = make_uint4(0, 0, 0, 0); v[u] = make_uint2(0, 0);
                    }
                }
#pragma unroll
                for (int u = 0; u < 4; u++) {
                    float x0 = __uint_as_float(v[u].x << 16), x1 = __uint_as_float(v[u].x & 0xffff0000u);
                    float x2 = __uint_as_float(v[u].y << 16), x3 = __uint_as_float(v[u].y & 0xffff0000u);
                    float c0 = __uint_as_float(r[u].y), c1 = __uint_as_float(r[u].z), c2 = __uint_as_float(r[u].w);
                    S[h][0][0] = fmaf(c0, x0, S[h][0][0]); S[h][0][1] = fmaf(c0, x1, S[h][0][1]);
                    S[h][0][2] = fmaf(c0, x2, S[h][0][2]); S[h][0][3] = fmaf(c0, x3, S[h][0][3]);
                    S[h][1][0] = fmaf(c1, x0, S[h][1][0]); S[h][1][1] = fmaf(c1, x1, S[h][1][1]);
                    S[h][1][2] = fmaf(c1, x2, S[h][1][2]); S[h][1][3] = fmaf(c1, x3, S[h][1][3]);
                    S[h][2][0] = fmaf(c2, x0, S[h][2][0]); S[h][2][1] = fmaf(c2, x1, S[h][2][1]);
                    S[h][2][2] = fmaf(c2, x2, S[h][2][2]); S[h][2][3] = fmaf(c2, x3, S[h][2][3]);
                }
            }
        }
    } else {
        float* sacc = reinterpret_cast<float*>(srec);
        for (int i = tid; i < EB * 48; i += P2_THREADS) sacc[i] = 0.f;
        __syncthreads();
        for (int i = tid; i < T; i += P2_THREADS) {
            int o = idx_out[i];
            if ((o >> EB_LOG) == b) {
                float an = bf16_bits_to_f(angle[i]);
                float c[3] = {cbf_val(f0, an), cbf_val(f1, an), cbf_val(f2, an)};
                const uint16_t* row = m + (size_t)idx_in[i] * 16;
                float* dst = sacc + (o & (EB - 1)) * 48;
                for (int k = 0; k < 16; k++) {
                    float x = bf16_bits_to_f(row[k]);
                    atomicAdd(dst + k, c[0] * x);
                    atomicAdd(dst + 16 + k, c[1] * x);
                    atomicAdd(dst + 32 + k, c[2] * x);
                }
            }
        }
        __syncthreads();
#pragma unroll
        for (int h = 0; h < 2; h++) {
            const int el = 16 * warp + 8 * h + g;
#pragma unroll
            for (int l = 0; l < 3; l++)
#pragma unroll
                for (int j = 0; j < 4; j++) S[h][l][j] = sacc[el * 48 + l * 16 + 4 * t + j];
        }
    }

    const int eA = b * EB + 16 * warp + g;
    const int eB = eA + 8;
    const bool okA = eA < E, okB = eB < E;

    const float cA = bf16_bits_to_f(centers[2 * t]), cB = bf16_bits_to_f(centers[2 * t + 1]);
    const float dA = okA ? bf16_bits_to_f(dist[eA]) : 0.f;
    const float dB = okB ? bf16_bits_to_f(dist[eB]) : 0.f;
    const uint32_t ra0 = pack_bf16(rbf_val(dA, cA), rbf_val(dA, cB));
    const uint32_t ra1 = pack_bf16(rbf_val(dB, cA), rbf_val(dB, cB));

    auto ld2 = [](const uint16_t* p0, const uint16_t* p1) -> uint32_t {
        return (uint32_t)__ldg(p0) | ((uint32_t)__ldg(p1) << 16);
    };

    float y[3][2][4];
#pragma unroll
    for (int tl = 0; tl < 3; tl++)
#pragma unroll
        for (int j = 0; j < 2; j++)
#pragma unroll
            for (int i = 0; i < 4; i++) y[tl][j][i] = 0.f;
    {
        uint32_t wd[2][2];
#pragma unroll
        for (int j = 0; j < 2; j++) {
            wd[j][0] = ld2(w_down + (4 * t + 0) * 16 + 8 * j + g, w_down + (4 * t + 1) * 16 + 8 * j + g);
            wd[j][1] = ld2(w_down + (4 * t + 2) * 16 + 8 * j + g, w_down + (4 * t + 3) * 16 + 8 * j + g);
        }
#pragma unroll
        for (int tl = 0; tl < 3; tl++) {
            const float* P = (tl == 0) ? S[0][0] : (tl == 1) ? S[1][0] : S[0][2];
            const float* Q = (tl == 0) ? S[0][1] : (tl == 1) ? S[1][1] : S[1][2];
            uint32_t h0 = pack_bf16(P[0], P[1]), h1 = pack_bf16(Q[0], Q[1]);
            uint32_t h2 = pack_bf16(P[2], P[3]), h3 = pack_bf16(Q[2], Q[3]);
            uint32_t l0 = pack_bf16(P[0] - __uint_as_float(h0 << 16), P[1] - __uint_as_float(h0 & 0xffff0000u));
            uint32_t l1 = pack_bf16(Q[0] - __uint_as_float(h1 << 16), Q[1] - __uint_as_float(h1 & 0xffff0000u));
            uint32_t l2 = pack_bf16(P[2] - __uint_as_float(h2 << 16), P[3] - __uint_as_float(h2 & 0xffff0000u));
            uint32_t l3 = pack_bf16(Q[2] - __uint_as_float(h3 << 16), Q[3] - __uint_as_float(h3 & 0xffff0000u));
#pragma unroll
            for (int j = 0; j < 2; j++) {
                mma16816(y[tl][j], h0, h1, h2, h3, wd[j][0], wd[j][1]);
                mma16816(y[tl][j], l0, l1, l2, l3, wd[j][0], wd[j][1]);
            }
        }
    }
    float aggA[2][2] = {{0.f, 0.f}, {0.f, 0.f}}, aggB[2][2] = {{0.f, 0.f}, {0.f, 0.f}};
#pragma unroll
    for (int l = 0; l < 3; l++) {
#pragma unroll
        for (int j = 0; j < 2; j++) {
            uint32_t ws = ld2(w_sbf + (3 * (2 * t) + l) * 16 + 8 * j + g, w_sbf + (3 * (2 * t + 1) + l) * 16 + 8 * j + g);
            float G[4] = {0.f, 0.f, 0.f, 0.f};
            mma1688(G, ra0, ra1, ws);
            float ya0, ya1, yb0, yb1;
            if (l == 0)      { ya0 = y[0][j][0]; ya1 = y[0][j][1]; yb0 = y[1][j][0]; yb1 = y[1][j][1]; }
            else if (l == 1) { ya0 = y[0][j][2]; ya1 = y[0][j][3]; yb0 = y[1][j][2]; yb1 = y[1][j][3]; }
            else             { ya0 = y[2][j][0]; ya1 = y[2][j][1]; yb0 = y[2][j][2]; yb1 = y[2][j][3]; }
            aggA[j][0] = fmaf(ya0, G[0], aggA[j][0]); aggA[j][1] = fmaf(ya1, G[1], aggA[j][1]);
            aggB[j][0] = fmaf(yb0, G[2], aggB[j][0]); aggB[j][1] = fmaf(yb1, G[3], aggB[j][1]);
        }
    }
    float u[2][4], rw[2][4];
    {
        uint32_t h0 = pack_bf16(aggA[0][0], aggA[0][1]), h1 = pack_bf16(aggB[0][0], aggB[0][1]);
        uint32_t h2 = pack_bf16(aggA[1][0], aggA[1][1]), h3 = pack_bf16(aggB[1][0], aggB[1][1]);
        uint32_t l0 = pack_bf16(aggA[0][0] - __uint_as_float(h0 << 16), aggA[0][1] - __uint_as_float(h0 & 0xffff0000u));
        uint32_t l1 = pack_bf16(aggB[0][0] - __uint_as_float(h1 << 16), aggB[0][1] - __uint_as_float(h1 & 0xffff0000u));
        uint32_t l2 = pack_bf16(aggA[1][0] - __uint_as_float(h2 << 16), aggA[1][1] - __uint_as_float(h2 & 0xffff0000u));
        uint32_t l3 = pack_bf16(aggB[1][0] - __uint_as_float(h3 << 16), aggB[1][1] - __uint_as_float(h3 & 0xffff0000u));
#pragma unroll
        for (int j = 0; j < 2; j++) {
            const int col = 4 * (g >> 1) + 2 * j + (g & 1);
            uint32_t b0 = ld2(w_up + (2 * t) * 16 + col, w_up + (2 * t + 1) * 16 + col);
            uint32_t b1 = ld2(w_up + (2 * t + 8) * 16 + col, w_up + (2 * t + 9) * 16 + col);
            uint32_t br = ld2(w_rbf + (2 * t) * 16 + col, w_rbf + (2 * t + 1) * 16 + col);
#pragma unroll
            for (int i = 0; i < 4; i++) { u[j][i] = 0.f; rw[j][i] = 0.f; }
            mma16816(u[j], h0, h1, h2, h3, b0, b1);
            mma16816(u[j], l0, l1, l2, l3, b0, b1);
            mma1688(rw[j], ra0, ra1, br);
        }
    }
    if (okA) {
        uint2 mv = __ldg(reinterpret_cast<const uint2*>(m + (size_t)eA * 16 + 4 * t));
        float o0 = fmaf(u[0][0], rw[0][0], __uint_as_float(mv.x << 16));
        float o1 = fmaf(u[0][1], rw[0][1], __uint_as_float(mv.x & 0xffff0000u));
        float o2 = fmaf(u[1][0], rw[1][0], __uint_as_float(mv.y << 16));
        float o3 = fmaf(u[1][1], rw[1][1], __uint_as_float(mv.y & 0xffff0000u));
        *reinterpret_cast<uint2*>(out + (size_t)eA * 16 + 4 * t) = make_uint2(pack_bf16(o0, o1), pack_bf16(o2, o3));
    }
    if (okB) {
        uint2 mv = __ldg(reinterpret_cast<const uint2*>(m + (size_t)eB * 16 + 4 * t));
        float o0 = fmaf(u[0][2], rw[0][2], __uint_as_float(mv.x << 16));
        float o1 = fmaf(u[0][3], rw[0][3], __uint_as_float(mv.x & 0xffff0000u));
        float o2 = fmaf(u[1][2], rw[1][2], __uint_as_float(mv.y << 16));
        float o3 = fmaf(u[1][3], rw[1][3], __uint_as_float(mv.y & 0xffff0000u));
        *reinterpret_cast<uint2*>(out + (size_t)eB * 16 + 4 * t) = make_uint2(pack_bf16(o0, o1), pack_bf16(o2, o3));
    }
}

}

extern "C" void kernel_launch(void* const* d_in, const int* in_sizes, int n_in,
                              void* d_out, int out_size) {
    const uint16_t* m        = (const uint16_t*)d_in[0];
    const int*      idx_in   = (const int*)d_in[1];
    const int*      idx_out  = (const int*)d_in[2];
    const uint16_t* dist     = (const uint16_t*)d_in[3];
    const uint16_t* angle    = (const uint16_t*)d_in[4];
    const uint16_t* centers  = (const uint16_t*)d_in[5];
    const uint16_t* ang_freq = (const uint16_t*)d_in[6];
    const uint16_t* w_rbf    = (const uint16_t*)d_in[7];
    const uint16_t* w_sbf    = (const uint16_t*)d_in[8];
    const uint16_t* w_down   = (const uint16_t*)d_in[9];
    const uint16_t* w_up     = (const uint16_t*)d_in[10];
    uint16_t* out = (uint16_t*)d_out;
    const int E = in_sizes[3];
    const int T = in_sizes[1];

    static bool init = false;
    if (!init) {
        cudaFuncSetAttribute(part_kernel, cudaFuncAttributeMaxDynamicSharedMemorySize, STAGE_CAP * 8);
        cudaFuncSetAttribute(edge_kernel, cudaFuncAttributeMaxDynamicSharedMemorySize, CAP * 16);
        init = true;
    }
    const int nb = (E + EB - 1) / EB;
    part_kernel<<<(T + C1 - 1) / C1, P1_THREADS, STAGE_CAP * 8>>>(idx_in, idx_out, angle, T);
    edge_kernel<<<nb, P2_THREADS, CAP * 16>>>(m, idx_in, idx_out, dist, angle, centers, ang_freq,
                                              w_rbf, w_sbf, w_down, w_up, out, E, T);
}
```

```cpp
#include <cuda_runtime.h>
#include <cuda_bf16.h>
#include <stdint.h>

namespace {

constexpr int kMaxE   = 400000;
constexpr int IDX_BITS = 19;
constexpr int EB_LOG  = 8;
constexpr int EB      = 1 << EB_LOG;
constexpr int NB_MAX  = (kMaxE + EB - 1) / EB;
constexpr int NB_PAD  = 2048;
constexpr int CAP     = 4608;
constexpr int CAPR    = 6144;
constexpr int STAGE_CAP = 11264;

constexpr int P1_THREADS = 512;
constexpr int P1_RPT     = 16;
constexpr int C1         = P1_THREADS * P1_RPT;

constexpr int P2_THREADS = 512;
constexpr int P2_RPT     = CAPR / P2_THREADS;

__device__ uint32_t g_cnt[NB_PAD];
__device__ __align__(128) uint2 g_q[(size_t)NB_MAX * CAPR];

__device__ __forceinline__ int4 ld_stream4(const int4* p) { return __ldcs(p); }
__device__ __forceinline__ uint2 ld_stream2(const uint2* p) { return __ldcs(p); }

__device__ __forceinline__ float bf16r(float x) { return __bfloat162float(__float2bfloat16_rn(x)); }
__device__ __forceinline__ float bf16_bits_to_f(uint32_t h) { return __uint_as_float(h << 16); }
__device__ __forceinline__ uint32_t pack_bf16(float lo, float hi) {
    __nv_bfloat162 v = __floats2bfloat162_rn(lo, hi);
    return *reinterpret_cast<uint32_t*>(&v);
}

__device__ __noinline__ float cos_slow(float x) { return cosf(x); }
__device__ __forceinline__ float cos_acc(float x) {
    if (fabsf(x) > 1000.f) return cos_slow(x);
    float k = rintf(x * 0.15915494309189535f);
    float r = fmaf(k, -6.28318548202514648f, x);
    r = fmaf(k, 1.7484555314695172e-7f, r);
    return __cosf(r);
}
__device__ __forceinline__ float cbf_val(float freq, float ang) {
    return bf16r(cos_acc(bf16r(freq * ang)));
}
__device__ __forceinline__ float rbf_val(float d, float c) {
    float x = bf16r(d - c);
    float s = bf16r(x * x);
    float a = bf16r(-10.f * s);
    return bf16r(expf(a));
}

__device__ __forceinline__ void mma16816(float* d, uint32_t a0, uint32_t a1, uint32_t a2, uint32_t a3,
                                         uint32_t b0, uint32_t b1) {
    asm volatile("mma.sync.aligned.m16n8k16.row.col.f32.bf16.bf16.f32 {%0,%1,%2,%3}, {%4,%5,%6,%7}, {%8,%9}, {%0,%1,%2,%3};"
                 : "+f"(d[0]), "+f"(d[1]), "+f"(d[2]), "+f"(d[3])
                 : "r"(a0), "r"(a1), "r"(a2), "r"(a3), "r"(b0), "r"(b1));
}
__device__ __forceinline__ void mma1688(float* d, uint32_t a0, uint32_t a1, uint32_t b0) {
    asm volatile("mma.sync.aligned.m16n8k8.row.col.f32.bf16.bf16.f32 {%0,%1,%2,%3}, {%4,%5}, {%6}, {%0,%1,%2,%3};"
                 : "+f"(d[0]), "+f"(d[1]), "+f"(d[2]), "+f"(d[3])
                 : "r"(a0), "r"(a1), "r"(b0));
}

__global__ void __launch_bounds__(P1_THREADS, 2)
part_kernel(const int* __restrict__ idx_in, const int* __restrict__ idx_out,
            const uint16_t* __restrict__ angle, int T)
{
    extern __shared__ __align__(16) uint2 stage[];
    __shared__ __align__(16) uint32_t s_off[NB_PAD];
    __shared__ __align__(16) int      s_delta[NB_PAD];
    __shared__ uint32_t s_warp[P1_THREADS / 32];

    const int tid = threadIdx.x;
    const int base = blockIdx.x * C1;

    uint32_t rx[16], ry[16];
    {
        int4 o[4], in[4];
        uint2 a[4];
#pragma unroll
        for (int j = 0; j < 4; j++) {
            int v = base / 4 + j * P1_THREADS + tid;
            if (v * 4 < T) {
                o[j]  = ld_stream4(reinterpret_cast<const int4*>(idx_out) + v);
                in[j] = ld_stream4(reinterpret_cast<const int4*>(idx_in) + v);
                a[j]  = ld_stream2(reinterpret_cast<const uint2*>(angle) + v);
            } else {
                o[j] = make_int4(-1, -1, -1, -1); in[j] = make_int4(0, 0, 0, 0); a[j] = make_uint2(0, 0);
            }
        }
        reinterpret_cast<uint4*>(s_off)[tid] = make_uint4(0, 0, 0, 0);
        __syncthreads();
#pragma unroll
        for (int j = 0; j < 4; j++) {
            const int ov[4] = {o[j].x, o[j].y, o[j].z, o[j].w};
            const int iv[4] = {in[j].x, in[j].y, in[j].z, in[j].w};
            const uint32_t av[4] = {a[j].x & 0xffffu, a[j].x >> 16, a[j].y & 0xffffu, a[j].y >> 16};
#pragma unroll
            for (int k = 0; k < 4; k++) {
                uint32_t bb = ((uint32_t)ov[k] >> EB_LOG) & 0xffffu;
                rx[j * 4 + k] = (uint32_t)iv[k] | ((uint32_t)(ov[k] & (EB - 1)) << IDX_BITS);
                ry[j * 4 + k] = av[k] | (bb << 16);
                if (ov[k] >= 0) atomicAdd(&s_off[bb], 1u);
            }
        }
    }
    __syncthreads();

    const uint4 c = reinterpret_cast<uint4*>(s_off)[tid];
    const uint4 cp = make_uint4((c.x + 3u) & ~3u, (c.y + 3u) & ~3u, (c.z + 3u) & ~3u, (c.w + 3u) & ~3u);
    uint32_t sum = cp.x + cp.y + cp.z + cp.w;
    uint32_t inc = sum;
#pragma unroll
    for (int d = 1; d < 32; d <<= 1) {
        uint32_t t = __shfl_up_sync(0xffffffffu, inc, d);
        if ((tid & 31) >= d) inc += t;
    }
    if ((tid & 31) == 31) s_warp[tid >> 5] = inc;
    uint32_t g0 = cp.x ? atomicAdd(&g_cnt[4 * tid + 0], cp.x) : 0u;
    uint32_t g1 = cp.y ? atomicAdd(&g_cnt[4 * tid + 1], cp.y) : 0u;
    uint32_t g2 = cp.z ? atomicAdd(&g_cnt[4 * tid + 2], cp.z) : 0u;
    uint32_t g3 = cp.w ? atomicAdd(&g_cnt[4 * tid + 3], cp.w) : 0u;
    __syncthreads();
    uint32_t wpre = 0, total = 0;
#pragma unroll
    for (int w = 0; w < P1_THREADS / 32; w++) { uint32_t x = s_warp[w]; wpre += (w < (tid >> 5)) ? x : 0u; total += x; }
    uint32_t ex = wpre + inc - sum;
    const uint4 off = make_uint4(ex, ex + cp.x, ex + cp.x + cp.y, ex + cp.x + cp.y + cp.z);
    reinterpret_cast<uint4*>(s_off)[tid] = off;
    reinterpret_cast<int4*>(s_delta)[tid] =
        make_int4((int)(g0 - off.x), (int)(g1 - off.y), (int)(g2 - off.z), (int)(g3 - off.w));
    {
        const uint32_t cc[4] = {c.x, c.y, c.z, c.w}, pp[4] = {cp.x, cp.y, cp.z, cp.w};
        const uint32_t oo[4] = {off.x, off.y, off.z, off.w}, gg[4] = {g0, g1, g2, g3};
#pragma unroll
        for (int k = 0; k < 4; k++) {
            for (uint32_t r = cc[k]; r < pp[k]; r++) {
                uint2 d = make_uint2(0xffffffffu, (uint32_t)(4 * tid + k) << 16);
                if (oo[k] + r < (uint32_t)STAGE_CAP) stage[oo[k] + r] = d;
                else if (gg[k] + r < (uint32_t)CAPR) g_q[(size_t)(4 * tid + k) * CAPR + gg[k] + r] = d;
            }
        }
    }
    __syncthreads();

#pragma unroll
    for (int k = 0; k < 16; k++) {
        uint32_t b = ry[k] >> 16;
        if (b != 0xffffu) {
            uint32_t p = atomicAdd(&s_off[b], 1u);
            uint2 r = make_uint2(rx[k], ry[k]);
            if (p < (uint32_t)STAGE_CAP) stage[p] = r;
            else {
                uint32_t gp = p + s_delta[b];
                if (gp < (uint32_t)CAPR) g_q[(size_t)b * CAPR + gp] = r;
            }
        }
    }
    __syncthreads();

    const int n = min((int)total, STAGE_CAP);
#pragma unroll 4
    for (int i = tid; i < n; i += P1_THREADS) {
        uint2 r = stage[i];
        uint32_t b = r.y >> 16;
        uint32_t p = (uint32_t)(i + s_delta[b]);
        if (p < (uint32_t)CAPR) g_q[(size_t)b * CAPR + p] = r;
    }
}

__global__ void __launch_bounds__(P2_THREADS, 2)
edge_kernel(const uint16_t* __restrict__ m, const int* __restrict__ idx_in, const int* __restrict__ idx_out,
            const uint16_t* __restrict__ dist, const uint16_t* __restrict__ angle,
            const uint16_t* __restrict__ centers, const uint16_t* __restrict__ ang_freq,
            const uint16_t* __restrict__ w_rbf, const uint16_t* __restrict__ w_sbf,
            const uint16_t* __restrict__ w_down, const uint16_t* __restrict__ w_up,
            uint16_t* __restrict__ out, int E, int T)
{
    extern __shared__ __align__(16) uint4 srec[];
    __shared__ uint32_t s_start[EB + 1];
    __shared__ uint32_t s_wsum[EB / 32];
    __shared__ uint32_t s_n;

    const int tid  = threadIdx.x;
    const int lane = tid & 31;
    const int warp = tid >> 5;
    const int g    = lane >> 2;
    const int t    = lane & 3;
    const int b    = blockIdx.x;

    if (tid == 0) { s_n = g_cnt[b]; g_cnt[b] = 0; }
    if (tid < EB) s_start[tid] = 0;
    const float f0 = bf16_bits_to_f(ang_freq[0]);
    const float f1 = bf16_bits_to_f(ang_freq[1]);
    const float f2 = bf16_bits_to_f(ang_freq[2]);
    __syncthreads();
    const uint32_t n = s_n;

    float S[2][3][4];
#pragma unroll
    for (int h = 0; h < 2; h++)
#pragma unroll
        for (int l = 0; l < 3; l++)
#pragma unroll
            for (int j = 0; j < 4; j++) S[h][l][j] = 0.f;

    bool fast = n <= (uint32_t)CAPR;
    uint32_t w[P2_RPT], av[P2_RPT], rk[P2_RPT];
    if (fast) {
        const uint4* gq = reinterpret_cast<const uint4*>(g_q + (size_t)b * CAPR);
#pragma unroll
        for (int k = 0; k < P2_RPT / 2; k++) {
            uint32_t i = tid + k * P2_THREADS;
            uint4 v = make_uint4(0xffffffffu, 0, 0xffffffffu, 0);
            if (2 * i < n) v = __ldcs(gq + i);
            w[2 * k] = v.x; av[2 * k] = v.y & 0xffffu; w[2 * k + 1] = v.z; av[2 * k + 1] = v.w & 0xffffu;
        }
#pragma unroll
        for (int k = 0; k < P2_RPT; k++)
            if (w[k] != 0xffffffffu) rk[k] = atomicAdd(&s_start[w[k] >> IDX_BITS], 1u);
        __syncthreads();
        uint32_t cnt = 0, inc = 0;
        if (tid < EB) {
            cnt = s_start[tid];
            inc = cnt;
#pragma unroll
            for (int d = 1; d < 32; d <<= 1) {
                uint32_t x = __shfl_up_sync(0xffffffffu, inc, d);
                if (lane >= d) inc += x;
            }
            if (lane == 31) s_wsum[warp] = inc;
        }
        __syncthreads();
        if (tid < EB) {
            uint32_t pre = 0;
#pragma unroll
            for (int x = 0; x < EB / 32; x++) pre += (x < warp) ? s_wsum[x] : 0u;
            s_start[tid] = pre + inc - cnt;
            if (tid == EB - 1) s_start[EB] = pre + inc;
        }
        __syncthreads();
        fast = s_start[EB] <= (uint32_t)CAP;
    }
    if (fast) {
#pragma unroll
        for (int k = 0; k < P2_RPT; k++) {
            if (w[k] != 0xffffffffu) {
                uint32_t p = s_start[w[k] >> IDX_BITS] + rk[k];
                float an = bf16_bits_to_f(av[k]);
                srec[p] = make_uint4((w[k] & ((1u << IDX_BITS) - 1)) * 32u,
                                     __float_as_uint(cbf_val(f0, an)),
                                     __float_as_uint(cbf_val(f1, an)),
                                     __float_as_uint(cbf_val(f2, an)));
            }
        }
        __syncthreads();

        const char* mbase = reinterpret_cast<const char*>(m) + t * 8;
#pragma unroll
        for (int h = 0; h < 2; h++) {
            const int el = 16 * warp + 8 * h + g;
            const uint32_t s = s_start[el], en = s_start[el + 1];
            for (uint32_t i = s; i < en; i += 4) {
                uint4 r[4]; uint2 v[4];
#pragma unroll
                for (int u = 0; u < 4; u++) {
                    if (i + u < en) {
                        r[u] = srec[i + u];
                        v[u] = __ldg(reinterpret_cast<const uint2*>(mbase + r[u].x));
                    } else {
                        r[u] = make_uint4(0, 0, 0, 0); v[u] = make_uint2(0, 0);
                    }
                }
#pragma unroll
                for (int u = 0; u < 4; u++) {
                    float x0 = __uint_as_float(v[u].x << 16), x1 = __uint_as_float(v[u].x & 0xffff0000u);
                    float x2 = __uint_as_float(v[u].y << 16), x3 = __uint_as_float(v[u].y & 0xffff0000u);
                    float c0 = __uint_as_float(r[u].y), c1 = __uint_as_float(r[u].z), c2 = __uint_as_float(r[u].w);
                    S[h][0][0] = fmaf(c0, x0, S[h][0][0]); S[h][0][1] = fmaf(c0, x1, S[h][0][1]);
                    S[h][0][2] = fmaf(c0, x2, S[h][0][2]); S[h][0][3] = fmaf(c0, x3, S[h][0][3]);
                    S[h][1][0] = fmaf(c1, x0, S[h][1][0]); S[h][1][1] = fmaf(c1, x1, S[h][1][1]);
                    S[h][1][2] = fmaf(c1, x2, S[h][1][2]); S[h][1][3] = fmaf(c1, x3, S[h][1][3]);
                    S[h][2][0] = fmaf(c2, x0, S[h][2][0]); S[h][2][1] = fmaf(c2, x1, S[h][2][1]);
                    S[h][2][2] = fmaf(c2, x2, S[h][2][2]); S[h][2][3] = fmaf(c2, x3, S[h][2][3]);
                }
            }
        }
    } else {
        float* sacc = reinterpret_cast<float*>(srec);
        for (int i = tid; i < EB * 48; i += P2_THREADS) sacc[i] = 0.f;
        __syncthreads();
        for (int i = tid; i < T; i += P2_THREADS) {
            int o = idx_out[i];
            if ((o >> EB_LOG) == b) {
                float an = bf16_bits_to_f(angle[i]);
                float c[3] = {cbf_val(f0, an), cbf_val(f1, an), cbf_val(f2, an)};
                const uint16_t* row = m + (size_t)idx_in[i] * 16;
                float* dst = sacc + (o & (EB - 1)) * 48;
                for (int k = 0; k < 16; k++) {
                    float x = bf16_bits_to_f(row[k]);
                    atomicAdd(dst + k, c[0] * x);
                    atomicAdd(dst + 16 + k, c[1] * x);
                    atomicAdd(dst + 32 + k, c[2] * x);
                }
            }
        }
        __syncthreads();
#pragma unroll
        for (int h = 0; h < 2; h++) {
            const int el = 16 * warp + 8 * h + g;
#pragma unroll
            for (int l = 0; l < 3; l++)
#pragma unroll
                for (int j = 0; j < 4; j++) S[h][l][j] = sacc[el * 48 + l * 16 + 4 * t + j];
        }
    }

    const int eA = b * EB + 16 * warp + g;
    const int eB = eA + 8;
    const bool okA = eA < E, okB = eB < E;

    const float cA = bf16_bits_to_f(centers[2 * t]), cB = bf16_bits_to_f(centers[2 * t + 1]);
    const float dA = okA ? bf16_bits_to_f(dist[eA]) : 0.f;
    const float dB = okB ? bf16_bits_to_f(dist[eB]) : 0.f;
    const uint32_t ra0 = pack_bf16(rbf_val(dA, cA), rbf_val(dA, cB));
    const uint32_t ra1 = pack_bf16(rbf_val(dB, cA), rbf_val(dB, cB));

    auto ld2 = [](const uint16_t* p0, const uint16_t* p1) -> uint32_t {
        return (uint32_t)__ldg(p0) | ((uint32_t)__ldg(p1) << 16);
    };

    float y[3][2][4];
#pragma unroll
    for (int tl = 0; tl < 3; tl++)
#pragma unroll
        for (int j = 0; j < 2; j++)
#pragma unroll
            for (int i = 0; i < 4; i++) y[tl][j][i] = 0.f;
    {
        uint32_t wd[2][2];
#pragma unroll
        for (int j = 0; j < 2; j++) {
            wd[j][0] = ld2(w_down + (4 * t + 0) * 16 + 8 * j + g, w_down + (4 * t + 1) * 16 + 8 * j + g);
            wd[j][1] = ld2(w_down + (4 * t + 2) * 16 + 8 * j + g, w_down + (4 * t + 3) * 16 + 8 * j + g);
        }
#pragma unroll
        for (int tl = 0; tl < 3; tl++) {
            const float* P = (tl == 0) ? S[0][0] : (tl == 1) ? S[1][0] : S[0][2];
            const float* Q = (tl == 0) ? S[0][1] : (tl == 1) ? S[1][1] : S[1][2];
            uint32_t h0 = pack_bf16(P[0], P[1]), h1 = pack_bf16(Q[0], Q[1]);
            uint32_t h2 = pack_bf16(P[2], P[3]), h3 = pack_bf16(Q[2], Q[3]);
            uint32_t l0 = pack_bf16(P[0] - __uint_as_float(h0 << 16), P[1] - __uint_as_float(h0 & 0xffff0000u));
            uint32_t l1 = pack_bf16(Q[0] - __uint_as_float(h1 << 16), Q[1] - __uint_as_float(h1 & 0xffff0000u));
            uint32_t l2 = pack_bf16(P[2] - __uint_as_float(h2 << 16), P[3] - __uint_as_float(h2 & 0xffff0000u));
            uint32_t l3 = pack_bf16(Q[2] - __uint_as_float(h3 << 16), Q[3] - __uint_as_float(h3 & 0xffff0000u));
#pragma unroll
            for (int j = 0; j < 2; j++) {
                mma16816(y[tl][j], h0, h1, h2, h3, wd[j][0], wd[j][1]);
                mma16816(y[tl][j], l0, l1, l2, l3, wd[j][0], wd[j][1]);
            }
        }
    }
    float aggA[2][2] = {{0.f, 0.f}, {0.f, 0.f}}, aggB[2][2] = {{0.f, 0.f}, {0.f, 0.f}};
#pragma unroll
    for (int l = 0; l < 3; l++) {
#pragma unroll
        for (int j = 0; j < 2; j++) {
            uint32_t ws = ld2(w_sbf + (3 * (2 * t) + l) * 16 + 8 * j + g, w_sbf + (3 * (2 * t + 1) + l) * 16 + 8 * j + g);
            float G[4] = {0.f, 0.f, 0.f, 0.f};
            mma1688(G, ra0, ra1, ws);
            float ya0, ya1, yb0, yb1;
            if (l == 0)      { ya0 = y[0][j][0]; ya1 = y[0][j][1]; yb0 = y[1][j][0]; yb1 = y[1][j][1]; }
            else if (l == 1) { ya0 = y[0][j][2]; ya1 = y[0][j][3]; yb0 = y[1][j][2]; yb1 = y[1][j][3]; }
            else             { ya0 = y[2][j][0]; ya1 = y[2][j][1]; yb0 = y[2][j][2]; yb1 = y[2][j][3]; }
            aggA[j][0] = fmaf(ya0, G[0], aggA[j][0]); aggA[j][1] = fmaf(ya1, G[1], aggA[j][1]);
            aggB[j][0] = fmaf(yb0, G[2], aggB[j][0]); aggB[j][1] = fmaf(yb1, G[3], aggB[j][1]);
        }
    }
    float u[2][4], rw[2][4];
    {
        uint32_t h0 = pack_bf16(aggA[0][0], aggA[0][1]), h1 = pack_bf16(aggB[0][0], aggB[0][1]);
        uint32_t h2 = pack_bf16(aggA[1][0], aggA[1][1]), h3 = pack_bf16(aggB[1][0], aggB[1][1]);
        uint32_t l0 = pack_bf16(aggA[0][0] - __uint_as_float(h0 << 16), aggA[0][1] - __uint_as_float(h0 & 0xffff0000u));
        uint32_t l1 = pack_bf16(aggB[0][0] - __uint_as_float(h1 << 16), aggB[0][1] - __uint_as_float(h1 & 0xffff0000u));
        uint32_t l2 = pack_bf16(aggA[1][0] - __uint_as_float(h2 << 16), aggA[1][1] - __uint_as_float(h2 & 0xffff0000u));
        uint32_t l3 = pack_bf16(aggB[1][0] - __uint_as_float(h3 << 16), aggB[1][1] - __uint_as_float(h3 & 0xffff0000u));
#pragma unroll
        for (int j = 0; j < 2; j++) {
            const int col = 4 * (g >> 1) + 2 * j + (g & 1);
            uint32_t b0 = ld2(w_up + (2 * t) * 16 + col, w_up + (2 * t + 1) * 16 + col);
            uint32_t b1 = ld2(w_up + (2 * t + 8) * 16 + col, w_up + (2 * t + 9) * 16 + col);
            uint32_t br = ld2(w_rbf + (2 * t) * 16 + col, w_rbf + (2 * t + 1) * 16 + col);
#pragma unroll
            for (int i = 0; i < 4; i++) { u[j][i] = 0.f; rw[j][i] = 0.f; }
            mma16816(u[j], h0, h1, h2, h3, b0, b1);
            mma16816(u[j], l0, l1, l2, l3, b0, b1);
            mma1688(rw[j], ra0, ra1, br);
        }
    }
    if (okA) {
        uint2 mv = __ldg(reinterpret_cast<const uint2*>(m + (size_t)eA * 16 + 4 * t));
        float o0 = fmaf(u[0][0], rw[0][0], __uint_as_float(mv.x << 16));
        float o1 = fmaf(u[0][1], rw[0][1], __uint_as_float(mv.x & 0xffff0000u));
        float o2 = fmaf(u[1][0], rw[1][0], __uint_as_float(mv.y << 16));
        float o3 = fmaf(u[1][1], rw[1][1], __uint_as_float(mv.y & 0xffff0000u));
        *reinterpret_cast<uint2*>(out + (size_t)eA * 16 + 4 * t) = make_uint2(pack_bf16(o0, o1), pack_bf16(o2, o3));
    }
    if (okB) {
        uint2 mv = __ldg(reinterpret_cast<const uint2*>(m + (size_t)eB * 16 + 4 * t));
        float o0 = fmaf(u[0][2], rw[0][2], __uint_as_float(mv.x << 16));
        float o1 = fmaf(u[0][3], rw[0][3], __uint_as_float(mv.x & 0xffff0000u));
        float o2 = fmaf(u[1][2], rw[1][2], __uint_as_float(mv.y << 16));
        float o3 = fmaf(u[1][3], rw[1][3], __uint_as_float(mv.y & 0xffff0000u));
        *reinterpret_cast<uint2*>(out + (size_t)eB * 16 + 4 * t) = make_uint2(pack_bf16(o0, o1), pack_bf16(o2, o3));
    }
}

}

extern "C" void kernel_launch(void* const* d_in, const int* in_sizes, int n_in,
                              void* d_out, int out_size) {
    const uint16_t* m        = (const uint16_t*)d_in[0];
    const int*      idx_in   = (const int*)d_in[1];
    const int*      idx_out  = (const int*)d_in[2];
    const uint16_t* dist     = (const uint16_t*)d_in[3];
    const uint16_t* angle    = (const uint16_t*)d_in[4];
    const uint16_t* centers  = (const uint16_t*)d_in[5];
    const uint16_t* ang_freq = (const uint16_t*)d_in[6];
    const uint16_t* w_rbf    = (const uint16_t*)d_in[7];
    const uint16_t* w_sbf    = (const uint16_t*)d_in[8];
    const uint16_t* w_down   = (const uint16_t*)d_in[9];
    const uint16_t* w_up     = (const uint16_t*)d_in[10];
    uint16_t* out = (uint16_t*)d_out;
    const int E = in_sizes[3];
    const int T = in_sizes[1];

    static bool init = false;
    if (!init) {
        cudaFuncSetAttribute(part_kernel, cudaFuncAttributeMaxDynamicSharedMemorySize, STAGE_CAP * 8);
        cudaFuncSetAttribute(edge_kernel, cudaFuncAttributeMaxDynamicSharedMemorySize, CAP * 16);
        init = true;
    }
    const int nb = (E + EB - 1) / EB;
    part_kernel<<<(T + C1 - 1) / C1, P1_THREADS, STAGE_CAP * 8>>>(idx_in, idx_out, angle, T);
    edge_kernel<<<nb, P2_THREADS, CAP * 16>>>(m, idx_in, idx_out, dist, angle, centers, ang_freq,
                                              w_rbf, w_sbf, w_down, w_up, out, E, T);
}
```

```cpp
#include <cuda_runtime.h>
#include <cuda_bf16.h>
#include <stdint.h>

namespace {

constexpr int kMaxE   = 400000;
constexpr int IDX_BITS = 19;
constexpr int EB_LOG  = 8;
constexpr int EB      = 1 << EB_LOG;
constexpr int NB_MAX  = (kMaxE + EB - 1) / EB;
constexpr int NB_PAD  = 2048;
constexpr int CAP     = 4608;
constexpr int CAPR    = 6144;
constexpr int STAGE_CAP = 11264;

constexpr int P1_THREADS = 512;
constexpr int P1_RPT     = 16;
constexpr int C1         = P1_THREADS * P1_RPT;

constexpr int P2_THREADS = 512;
constexpr int P2_RPT     = CAPR / P2_THREADS;

__device__ uint32_t g_cnt[NB_PAD];
__device__ __align__(128) uint2 g_q[(size_t)NB_MAX * CAPR];

__device__ __forceinline__ int4 ld_stream4(const int4* p) { return __ldcs(p); }
__device__ __forceinline__ uint2 ld_stream2(const uint2* p) { return __ldcs(p); }

__device__ __forceinline__ float bf16r(float x) { return __bfloat162float(__float2bfloat16_rn(x)); }
__device__ __forceinline__ float bf16_bits_to_f(uint32_t h) { return __uint_as_float(h << 16); }
__device__ __forceinline__ uint32_t pack_bf16(float lo, float hi) {
    __nv_bfloat162 v = __floats2bfloat162_rn(lo, hi);
    return *reinterpret_cast<uint32_t*>(&v);
}

__device__ __noinline__ float cos_slow(float x) { return cosf(x); }
__device__ __forceinline__ float cos_acc(float x) {
    if (fabsf(x) > 1000.f) return cos_slow(x);
    float k = rintf(x * 0.15915494309189535f);
    float r = fmaf(k, -6.28318548202514648f, x);
    r = fmaf(k, 1.7484555314695172e-7f, r);
    return __cosf(r);
}
__device__ __forceinline__ float cbf_val(float freq, float ang) {
    return bf16r(cos_acc(bf16r(freq * ang)));
}
__device__ __forceinline__ float rbf_val(float d, float c) {
    float x = bf16r(d - c);
    float s = bf16r(x * x);
    float a = bf16r(-10.f * s);
    return bf16r(expf(a));
}

__device__ __forceinline__ void mma16816(float* d, uint32_t a0, uint32_t a1, uint32_t a2, uint32_t a3,
                                         uint32_t b0, uint32_t b1) {
    asm volatile("mma.sync.aligned.m16n8k16.row.col.f32.bf16.bf16.f32 {%0,%1,%2,%3}, {%4,%5,%6,%7}, {%8,%9}, {%0,%1,%2,%3};"
                 : "+f"(d[0]), "+f"(d[1]), "+f"(d[2]), "+f"(d[3])
                 : "r"(a0), "r"(a1), "r"(a2), "r"(a3), "r"(b0), "r"(b1));
}
__device__ __forceinline__ void mma1688(float* d, uint32_t a0, uint32_t a1, uint32_t b0) {
    asm volatile("mma.sync.aligned.m16n8k8.row.col.f32.bf16.bf16.f32 {%0,%1,%2,%3}, {%4,%5}, {%6}, {%0,%1,%2,%3};"
                 : "+f"(d[0]), "+f"(d[1]), "+f"(d[2]), "+f"(d[3])
                 : "r"(a0), "r"(a1), "r"(b0));
}

__global__ void __launch_bounds__(P1_THREADS, 2)
part_kernel(const int* __restrict__ idx_in, const int* __restrict__ idx_out,
            const uint16_t* __restrict__ angle, int T)
{
    extern __shared__ __align__(16) uint2 stage[];
    __shared__ __align__(16) uint32_t s_off[NB_PAD];
    __shared__ __align__(16) int      s_delta[NB_PAD];
    __shared__ uint32_t s_warp[P1_THREADS / 32];

    const int tid = threadIdx.x;
    const int base = blockIdx.x * C1;

    uint32_t rx[16], ry[16];
    {
        int4 o[4], in[4];
        uint2 a[4];
#pragma unroll
        for (int j = 0; j < 4; j++) {
            int v = base / 4 + j * P1_THREADS + tid;
            if (v * 4 < T) {
                o[j]  = ld_stream4(reinterpret_cast<const int4*>(idx_out) + v);
                in[j] = ld_stream4(reinterpret_cast<const int4*>(idx_in) + v);
                a[j]  = ld_stream2(reinterpret_cast<const uint2*>(angle) + v);
            } else {
                o[j] = make_int4(-1, -1, -1, -1); in[j] = make_int4(0, 0, 0, 0); a[j] = make_uint2(0, 0);
            }
        }
        reinterpret_cast<uint4*>(s_off)[tid] = make_uint4(0, 0, 0, 0);
        __syncthreads();
#pragma unroll
        for (int j = 0; j < 4; j++) {
            const int ov[4] = {o[j].x, o[j].y, o[j].z, o[j].w};
            const int iv[4] = {in[j].x, in[j].y, in[j].z, in[j].w};
            const uint32_t av[4] = {a[j].x & 0xffffu, a[j].x >> 16, a[j].y & 0xffffu, a[j].y >> 16};
#pragma unroll
            for (int k = 0; k < 4; k++) {
                uint32_t bb = ((uint32_t)ov[k] >> EB_LOG) & 0xffffu;
                rx[j * 4 + k] = (uint32_t)iv[k] | ((uint32_t)(ov[k] & (EB - 1)) << IDX_BITS);
                ry[j * 4 + k] = av[k] | (bb << 16);
                if (ov[k] >= 0) atomicAdd(&s_off[bb], 1u);
            }
        }
    }
    __syncthreads();

    const uint4 c = reinterpret_cast<uint4*>(s_off)[tid];
    const uint4 cp = make_uint4((c.x + 3u) & ~3u, (c.y + 3u) & ~3u, (c.z + 3u) & ~3u, (c.w + 3u) & ~3u);
    uint32_t sum = cp.x + cp.y + cp.z + cp.w;
    uint32_t inc = sum;
#pragma unroll
    for (int d = 1; d < 32; d <<= 1) {
        uint32_t t = __shfl_up_sync(0xffffffffu, inc, d);
        if ((tid & 31) >= d) inc += t;
    }
    if ((tid & 31) == 31) s_warp[tid >> 5] = inc;
    uint32_t g0 = cp.x ? atomicAdd(&g_cnt[4 * tid + 0], cp.x) : 0u;
    uint32_t g1 = cp.y ? atomicAdd(&g_cnt[4 * tid + 1], cp.y) : 0u;
    uint32_t g2 = cp.z ? atomicAdd(&g_cnt[4 * tid + 2], cp.z) : 0u;
    uint32_t g3 = cp.w ? atomicAdd(&g_cnt[4 * tid + 3], cp.w) : 0u;
    __syncthreads();
    uint32_t wpre, total;
    {
        uint32_t x = ((tid & 31) < P1_THREADS / 32) ? s_warp[tid & 31] : 0u;
#pragma unroll
        for (int d = 1; d < P1_THREADS / 32; d <<= 1) {
            uint32_t t = __shfl_up_sync(0xffffffffu, x, d);
            if ((tid & 31) >= d) x += t;
        }
        total = __shfl_sync(0xffffffffu, x, P1_THREADS / 32 - 1);
        wpre = __shfl_sync(0xffffffffu, x, ((tid >> 5) + 31) & 31);
        if ((tid >> 5) == 0) wpre = 0;
    }
    uint32_t ex = wpre + inc - sum;
    const uint4 off = make_uint4(ex, ex + cp.x, ex + cp.x + cp.y, ex + cp.x + cp.y + cp.z);
    reinterpret_cast<uint4*>(s_off)[tid] = off;
    reinterpret_cast<int4*>(s_delta)[tid] =
        make_int4((int)(g0 - off.x), (int)(g1 - off.y), (int)(g2 - off.z), (int)(g3 - off.w));
    __syncthreads();

#pragma unroll
    for (int k = 0; k < 16; k++) {
        uint32_t b = ry[k] >> 16;
        if (b != 0xffffu) {
            uint32_t p = atomicAdd(&s_off[b], 1u);
            uint2 r = make_uint2(rx[k], ry[k]);
            if (p < (uint32_t)STAGE_CAP) stage[p] = r;
            else {
                uint32_t gp = p + s_delta[b];
                if (gp < (uint32_t)CAPR) g_q[(size_t)b * CAPR + gp] = r;
            }
        }
    }
    __syncthreads();
    {
        const uint4 cur = reinterpret_cast<uint4*>(s_off)[tid];
        const uint32_t cc[4] = {cur.x, cur.y, cur.z, cur.w};
#pragma unroll
        for (int k = 0; k < 4; k++) {
            for (uint32_t p = cc[k]; p & 3u; p++) {
                uint2 d = make_uint2(0xffffffffu, (uint32_t)(4 * tid + k) << 16);
                if (p < (uint32_t)STAGE_CAP) stage[p] = d;
                else {
                    uint32_t gp = p + s_delta[4 * tid + k];
                    if (gp < (uint32_t)CAPR) g_q[(size_t)(4 * tid + k) * CAPR + gp] = d;
                }
            }
        }
    }
    __syncthreads();

    const int n = min((int)total, STAGE_CAP);
#pragma unroll 4
    for (int i = tid; i < n; i += P1_THREADS) {
        uint2 r = stage[i];
        uint32_t b = r.y >> 16;
        uint32_t p = (uint32_t)(i + s_delta[b]);
        if (p < (uint32_t)CAPR) g_q[(size_t)b * CAPR + p] = r;
    }
}

__global__ void __launch_bounds__(P2_THREADS, 2)
edge_kernel(const uint16_t* __restrict__ m, const int* __restrict__ idx_in, const int* __restrict__ idx_out,
            const uint16_t* __restrict__ dist, const uint16_t* __restrict__ angle,
            const uint16_t* __restrict__ centers, const uint16_t* __restrict__ ang_freq,
            const uint16_t* __restrict__ w_rbf, const uint16_t* __restrict__ w_sbf,
            const uint16_t* __restrict__ w_down, const uint16_t* __restrict__ w_up,
            uint16_t* __restrict__ out, int E, int T)
{
    extern __shared__ __align__(16) uint4 srec[];
    __shared__ uint32_t s_start[EB + 1];
    __shared__ uint32_t s_wsum[EB / 32];
    __shared__ uint32_t s_n;

    const int tid  = threadIdx.x;
    const int lane = tid & 31;
    const int warp = tid >> 5;
    const int g    = lane >> 2;
    const int t    = lane & 3;
    const int b    = blockIdx.x;

    if (tid == 0) { s_n = g_cnt[b]; g_cnt[b] = 0; }
    if (tid < EB) s_start[tid] = 0;
    const float f0 = bf16_bits_to_f(ang_freq[0]);
    const float f1 = bf16_bits_to_f(ang_freq[1]);
    const float f2 = bf16_bits_to_f(ang_freq[2]);
    __syncthreads();
    const uint32_t n = s_n;

    float S[2][3][4];
#pragma unroll
    for (int h = 0; h < 2; h++)
#pragma unroll
        for (int l = 0; l < 3; l++)
#pragma unroll
            for (int j = 0; j < 4; j++) S[h][l][j] = 0.f;

    bool fast = n <= (uint32_t)CAPR;
    uint32_t w[P2_RPT], av[P2_RPT], rk[P2_RPT];
    if (fast) {
        const uint4* gq = reinterpret_cast<const uint4*>(g_q + (size_t)b * CAPR);
#pragma unroll
        for (int k = 0; k < P2_RPT / 2; k++) {
            uint32_t i = tid + k * P2_THREADS;
            uint4 v = make_uint4(0xffffffffu, 0, 0xffffffffu, 0);
            if (2 * i < n) v = __ldcs(gq + i);
            w[2 * k] = v.x; av[2 * k] = v.y & 0xffffu; w[2 * k + 1] = v.z; av[2 * k + 1] = v.w & 0xffffu;
        }
#pragma unroll
        for (int k = 0; k < P2_RPT; k++)
            if (w[k] != 0xffffffffu) rk[k] = atomicAdd(&s_start[w[k] >> IDX_BITS], 1u);
        __syncthreads();
        uint32_t cnt = 0, inc = 0;
        if (tid < EB) {
            cnt = s_start[tid];
            inc = cnt;
#pragma unroll
            for (int d = 1; d < 32; d <<= 1) {
                uint32_t x = __shfl_up_sync(0xffffffffu, inc, d);
                if (lane >= d) inc += x;
            }
            if (lane == 31) s_wsum[warp] = inc;
        }
        __syncthreads();
        if (tid < EB) {
            uint32_t pre = 0;
#pragma unroll
            for (int x = 0; x < EB / 32; x++) pre += (x < warp) ? s_wsum[x] : 0u;
            s_start[tid] = pre + inc - cnt;
            if (tid == EB - 1) s_start[EB] = pre + inc;
        }
        __syncthreads();
        fast = s_start[EB] <= (uint32_t)CAP;
    }
    if (fast) {
#pragma unroll
        for (int k = 0; k < P2_RPT; k++) {
            if (w[k] != 0xffffffffu) {
                uint32_t p = s_start[w[k] >> IDX_BITS] + rk[k];
                float an = bf16_bits_to_f(av[k]);
                srec[p] = make_uint4((w[k] & ((1u << IDX_BITS) - 1)) * 32u,
                                     __float_as_uint(cbf_val(f0, an)),
                                     __float_as_uint(cbf_val(f1, an)),
                                     __float_as_uint(cbf_val(f2, an)));
            }
        }
        __syncthreads();

        const char* mbase = reinterpret_cast<const char*>(m) + t * 8;
#pragma unroll
        for (int h = 0; h < 2; h++) {
            const int el = 16 * warp + 8 * h + g;
            const uint32_t s = s_start[el], en = s_start[el + 1];
            for (uint32_t i = s; i < en; i += 4) {
                uint4 r[4]; uint2 v[4];
#pragma unroll
                for (int u = 0; u < 4; u++) {
                    if (i + u < en) {
                        r[u] = srec[i + u];
                        v[u] = __ldg(reinterpret_cast<const uint2*>(mbase + r[u].x));
                    } else {
                        r[u] = make_uint4(0, 0, 0, 0); v[u] = make_uint2(0, 0);
                    }
                }
#pragma unroll
                for (int u = 0; u < 4; u++) {
                    float x0 = __uint_as_float(v[u].x << 16), x1 = __uint_as_float(v[u].x & 0xffff0000u);
                    float x2 = __uint_as_float(v[u].y << 16), x3 = __uint_as_float(v[u].y & 0xffff0000u);
                    float c0 = __uint_as_float(r[u].y), c1 = __uint_as_float(r[u].z), c2 = __uint_as_float(r[u].w);
                    S[h][0][0] = fmaf(c0, x0, S[h][0][0]); S[h][0][1] = fmaf(c0, x1, S[h][0][1]);
                    S[h][0][2] = fmaf(c0, x2, S[h][0][2]); S[h][0][3] = fmaf(c0, x3, S[h][0][3]);
                    S[h][1][0] = fmaf(c1, x0, S[h][1][0]); S[h][1][1] = fmaf(c1, x1, S[h][1][1]);
                    S[h][1][2] = fmaf(c1, x2, S[h][1][2]); S[h][1][3] = fmaf(c1, x3, S[h][1][3]);
                    S[h][2][0] = fmaf(c2, x0, S[h][2][0]); S[h][2][1] = fmaf(c2, x1, S[h][2][1]);
                    S[h][2][2] = fmaf(c2, x2, S[h][2][2]); S[h][2][3] = fmaf(c2, x3, S[h][2][3]);
                }
            }
        }
    } else {
        float* sacc = reinterpret_cast<float*>(srec);
        for (int i = tid; i < EB * 48; i += P2_THREADS) sacc[i] = 0.f;
        __syncthreads();
        for (int i = tid; i < T; i += P2_THREADS) {
            int o = idx_out[i];
            if ((o >> EB_LOG) == b) {
                float an = bf16_bits_to_f(angle[i]);
                float c[3] = {cbf_val(f0, an), cbf_val(f1, an), cbf_val(f2, an)};
                const uint16_t* row = m + (size_t)idx_in[i] * 16;
                float* dst = sacc + (o & (EB - 1)) * 48;
                for (int k = 0; k < 16; k++) {
                    float x = bf16_bits_to_f(row[k]);
                    atomicAdd(dst + k, c[0] * x);
                    atomicAdd(dst + 16 + k, c[1] * x);
                    atomicAdd(dst + 32 + k, c[2] * x);
                }
            }
        }
        __syncthreads();
#pragma unroll
        for (int h = 0; h < 2; h++) {
            const int el = 16 * warp + 8 * h + g;
#pragma unroll
            for (int l = 0; l < 3; l++)
#pragma unroll
                for (int j = 0; j < 4; j++) S[h][l][j] = sacc[el * 48 + l * 16 + 4 * t + j];
        }
    }

    const int eA = b * EB + 16 * warp + g;
    const int eB = eA + 8;
    const bool okA = eA < E, okB = eB < E;

    const float cA = bf16_bits_to_f(centers[2 * t]), cB = bf16_bits_to_f(centers[2 * t + 1]);
    const float dA = okA ? bf16_bits_to_f(dist[eA]) : 0.f;
    const float dB = okB ? bf16_bits_to_f(dist[eB]) : 0.f;
    const uint32_t ra0 = pack_bf16(rbf_val(dA, cA), rbf_val(dA, cB));
    const uint32_t ra1 = pack_bf16(rbf_val(dB, cA), rbf_val(dB, cB));

    auto ld2 = [](const uint16_t* p0, const uint16_t* p1) -> uint32_t {
        return (uint32_t)__ldg(p0) | ((uint32_t)__ldg(p1) << 16);
    };

    float y[3][2][4];
#pragma unroll
    for (int tl = 0; tl < 3; tl++)
#pragma unroll
        for (int j = 0; j < 2; j++)
#pragma unroll
            for (int i = 0; i < 4; i++) y[tl][j][i] = 0.f;
    {
        uint32_t wd[2][2];
#pragma unroll
        for (int j = 0; j < 2; j++) {
            wd[j][0] = ld2(w_down + (4 * t + 0) * 16 + 8 * j + g, w_down + (4 * t + 1) * 16 + 8 * j + g);
            wd[j][1] = ld2(w_down + (4 * t + 2) * 16 + 8 * j + g, w_down + (4 * t + 3) * 16 + 8 * j + g);
        }
#pragma unroll
        for (int tl = 0; tl < 3; tl++) {
            const float* P = (tl == 0) ? S[0][0] : (tl == 1) ? S[1][0] : S[0][2];
            const float* Q = (tl == 0) ? S[0][1] : (tl == 1) ? S[1][1] : S[1][2];
            uint32_t h0 = pack_bf16(P[0], P[1]), h1 = pack_bf16(Q[0], Q[1]);
            uint32_t h2 = pack_bf16(P[2], P[3]), h3 = pack_bf16(Q[2], Q[3]);
            uint32_t l0 = pack_bf16(P[0] - __uint_as_float(h0 << 16), P[1] - __uint_as_float(h0 & 0xffff0000u));
            uint32_t l1 = pack_bf16(Q[0] - __uint_as_float(h1 << 16), Q[1] - __uint_as_float(h1 & 0xffff0000u));
            uint32_t l2 = pack_bf16(P[2] - __uint_as_float(h2 << 16), P[3] - __uint_as_float(h2 & 0xffff0000u));
            uint32_t l3 = pack_bf16(Q[2] - __uint_as_float(h3 << 16), Q[3] - __uint_as_float(h3 & 0xffff0000u));
#pragma unroll
            for (int j = 0; j < 2; j++) {
                mma16816(y[tl][j], h0, h1, h2, h3, wd[j][0], wd[j][1]);
                mma16816(y[tl][j], l0, l1, l2, l3, wd[j][0], wd[j][1]);
            }
        }
    }
    float aggA[2][2] = {{0.f, 0.f}, {0.f, 0.f}}, aggB[2][2] = {{0.f, 0.f}, {0.f, 0.f}};
#pragma unroll
    for (int l = 0; l < 3; l++) {
#pragma unroll
        for (int j = 0; j < 2; j++) {
            uint32_t ws = ld2(w_sbf + (3 * (2 * t) + l) * 16 + 8 * j + g, w_sbf + (3 * (2 * t + 1) + l) * 16 + 8 * j + g);
            float G[4] = {0.f, 0.f, 0.f, 0.f};
            mma1688(G, ra0, ra1, ws);
            float ya0, ya1, yb0, yb1;
            if (l == 0)      { ya0 = y[0][j][0]; ya1 = y[0][j][1]; yb0 = y[1][j][0]; yb1 = y[1][j][1]; }
            else if (l == 1) { ya0 = y[0][j][2]; ya1 = y[0][j][3]; yb0 = y[1][j][2]; yb1 = y[1][j][3]; }
            else             { ya0 = y[2][j][0]; ya1 = y[2][j][1]; yb0 = y[2][j][2]; yb1 = y[2][j][3]; }
            aggA[j][0] = fmaf(ya0, G[0], aggA[j][0]); aggA[j][1] = fmaf(ya1, G[1], aggA[j][1]);
            aggB[j][0] = fmaf(yb0, G[2], aggB[j][0]); aggB[j][1] = fmaf(yb1, G[3], aggB[j][1]);
        }
    }
    float u[2][4], rw[2][4];
    {
        uint32_t h0 = pack_bf16(aggA[0][0], aggA[0][1]), h1 = pack_bf16(aggB[0][0], aggB[0][1]);
        uint32_t h2 = pack_bf16(aggA[1][0], aggA[1][1]), h3 = pack_bf16(aggB[1][0], aggB[1][1]);
        uint32_t l0 = pack_bf16(aggA[0][0] - __uint_as_float(h0 << 16), aggA[0][1] - __uint_as_float(h0 & 0xffff0000u));
        uint32_t l1 = pack_bf16(aggB[0][0] - __uint_as_float(h1 << 16), aggB[0][1] - __uint_as_float(h1 & 0xffff0000u));
        uint32_t l2 = pack_bf16(aggA[1][0] - __uint_as_float(h2 << 16), aggA[1][1] - __uint_as_float(h2 & 0xffff0000u));
        uint32_t l3 = pack_bf16(aggB[1][0] - __uint_as_float(h3 << 16), aggB[1][1] - __uint_as_float(h3 & 0xffff0000u));
#pragma unroll
        for (int j = 0; j < 2; j++) {
            const int col = 4 * (g >> 1) + 2 * j + (g & 1);
            uint32_t b0 = ld2(w_up + (2 * t) * 16 + col, w_up + (2 * t + 1) * 16 + col);
            uint32_t b1 = ld2(w_up + (2 * t + 8) * 16 + col, w_up + (2 * t + 9) * 16 + col);
            uint32_t br = ld2(w_rbf + (2 * t) * 16 + col, w_rbf + (2 * t + 1) * 16 + col);
#pragma unroll
            for (int i = 0; i < 4; i++) { u[j][i] = 0.f; rw[j][i] = 0.f; }
            mma16816(u[j], h0, h1, h2, h3, b0, b1);
            mma16816(u[j], l0, l1, l2, l3, b0, b1);
            mma1688(rw[j], ra0, ra1, br);
        }
    }
    if (okA) {
        uint2 mv = __ldg(reinterpret_cast<const uint2*>(m + (size_t)eA * 16 + 4 * t));
        float o0 = fmaf(u[0][0], rw[0][0], __uint_as_float(mv.x << 16));
        float o1 = fmaf(u[0][1], rw[0][1], __uint_as_float(mv.x & 0xffff0000u));
        float o2 = fmaf(u[1][0], rw[1][0], __uint_as_float(mv.y << 16));
        float o3 = fmaf(u[1][1], rw[1][1], __uint_as_float(mv.y & 0xffff0000u));
        *reinterpret_cast<uint2*>(out + (size_t)eA * 16 + 4 * t) = make_uint2(pack_bf16(o0, o1), pack_bf16(o2, o3));
    }
    if (okB) {
        uint2 mv = __ldg(reinterpret_cast<const uint2*>(m + (size_t)eB * 16 + 4 * t));
        float o0 = fmaf(u[0][2], rw[0][2], __uint_as_float(mv.x << 16));
        float o1 = fmaf(u[0][3], rw[0][3], __uint_as_float(mv.x & 0xffff0000u));
        float o2 = fmaf(u[1][2], rw[1][2], __uint_as_float(mv.y << 16));
        float o3 = fmaf(u[1][3], rw[1][3], __uint_as_float(mv.y & 0xffff0000u));
        *reinterpret_cast<uint2*>(out + (size_t)eB * 16 + 4 * t) = make_uint2(pack_bf16(o0, o1), pack_bf16(o2, o3));
    }
}

}

extern "C" void kernel_launch(void* const* d_in, const int* in_sizes, int n_in,
                              void* d_out, int out_size) {
    const uint16_t* m        = (const uint16_t*)d_in[0];
    const int*      idx_in   = (const int*)d_in[1];
    const int*      idx_out  = (const int*)d_in[2];
    const uint16_t* dist     = (const uint16_t*)d_in[3];
    const uint16_t* angle    = (const uint16_t*)d_in[4];
    const uint16_t* centers  = (const uint16_t*)d_in[5];
    const uint16_t* ang_freq = (const uint16_t*)d_in[6];
    const uint16_t* w_rbf    = (const uint16_t*)d_in[7];
    const uint16_t* w_sbf    = (const uint16_t*)d_in[8];
    const uint16_t* w_down   = (const uint16_t*)d_in[9];
    const uint16_t* w_up     = (const uint16_t*)d_in[10];
    uint16_t* out = (uint16_t*)d_out;
    const int E = in_sizes[3];
    const int T = in_sizes[1];

    static bool init = false;
    if (!init) {
        cudaFuncSetAttribute(part_kernel, cudaFuncAttributeMaxDynamicSharedMemorySize, STAGE_CAP * 8);
        cudaFuncSetAttribute(edge_kernel, cudaFuncAttributeMaxDynamicSharedMemorySize, CAP * 16);
        init = true;
    }
    const int nb = (E + EB - 1) / EB;
    part_kernel<<<(T + C1 - 1) / C1, P1_THREADS, STAGE_CAP * 8>>>(idx_in, idx_out, angle, T);
    edge_kernel<<<nb, P2_THREADS, CAP * 16>>>(m, idx_in, idx_out, dist, angle, centers, ang_freq,
                                              w_rbf, w_sbf, w_down, w_up, out, E, T);
}
```

```cpp
#include <cuda_runtime.h>
#include <cuda_bf16.h>
#include <stdint.h>

namespace {

constexpr int kMaxE   = 400000;
constexpr int IDX_BITS = 19;
constexpr int EB_LOG  = 8;
constexpr int EB      = 1 << EB_LOG;
constexpr int NB_MAX  = (kMaxE + EB - 1) / EB;
constexpr int NB_PAD  = 2048;
constexpr int CAP     = 4608;
constexpr int CAPR    = 6144;
constexpr int NREP    = 4;
constexpr int CAPQ    = 1664;
constexpr int STAGE_CAP = 11264;

constexpr int P1_THREADS = 512;
constexpr int P1_RPT     = 16;
constexpr int C1         = P1_THREADS * P1_RPT;

constexpr int P2_THREADS = 512;
constexpr int P2_RPT     = CAPR / P2_THREADS;

__device__ uint32_t g_cnt[NREP * NB_PAD];
__device__ __align__(128) uint2 g_q[(size_t)NB_MAX * NREP * CAPQ];

__device__ __forceinline__ int4 ld_stream4(const int4* p) { return __ldcs(p); }
__device__ __forceinline__ uint2 ld_stream2(const uint2* p) { return __ldcs(p); }

__device__ __forceinline__ float bf16r(float x) { return __bfloat162float(__float2bfloat16_rn(x)); }
__device__ __forceinline__ float bf16_bits_to_f(uint32_t h) { return __uint_as_float(h << 16); }
__device__ __forceinline__ uint32_t pack_bf16(float lo, float hi) {
    __nv_bfloat162 v = __floats2bfloat162_rn(lo, hi);
    return *reinterpret_cast<uint32_t*>(&v);
}

__device__ __noinline__ float cos_slow(float x) { return cosf(x); }
__device__ __forceinline__ float cos_acc(float x) {
    if (fabsf(x) > 1000.f) return cos_slow(x);
    float k = rintf(x * 0.15915494309189535f);
    float r = fmaf(k, -6.28318548202514648f, x);
    r = fmaf(k, 1.7484555314695172e-7f, r);
    return __cosf(r);
}
__device__ __forceinline__ float cbf_val(float freq, float ang) {
    return bf16r(cos_acc(bf16r(freq * ang)));
}
__device__ __forceinline__ float rbf_val(float d, float c) {
    float x = bf16r(d - c);
    float s = bf16r(x * x);
    float a = bf16r(-10.f * s);
    return bf16r(expf(a));
}

__device__ __forceinline__ void mma16816(float* d, uint32_t a0, uint32_t a1, uint32_t a2, uint32_t a3,
                                         uint32_t b0, uint32_t b1) {
    asm volatile("mma.sync.aligned.m16n8k16.row.col.f32.bf16.bf16.f32 {%0,%1,%2,%3}, {%4,%5,%6,%7}, {%8,%9}, {%0,%1,%2,%3};"
                 : "+f"(d[0]), "+f"(d[1]), "+f"(d[2]), "+f"(d[3])
                 : "r"(a0), "r"(a1), "r"(a2), "r"(a3), "r"(b0), "r"(b1));
}
__device__ __forceinline__ void mma1688(float* d, uint32_t a0, uint32_t a1, uint32_t b0) {
    asm volatile("mma.sync.aligned.m16n8k8.row.col.f32.bf16.bf16.f32 {%0,%1,%2,%3}, {%4,%5}, {%6}, {%0,%1,%2,%3};"
                 : "+f"(d[0]), "+f"(d[1]), "+f"(d[2]), "+f"(d[3])
                 : "r"(a0), "r"(a1), "r"(b0));
}

__global__ void __launch_bounds__(P1_THREADS, 2)
part_kernel(const int* __restrict__ idx_in, const int* __restrict__ idx_out,
            const uint16_t* __restrict__ angle, int T)
{
    extern __shared__ __align__(16) uint2 stage[];
    __shared__ __align__(16) uint32_t s_off[NB_PAD];
    __shared__ __align__(16) int      s_delta[NB_PAD];
    __shared__ uint32_t s_warp[P1_THREADS / 32];

    const int tid = threadIdx.x;
    const int base = blockIdx.x * C1;

    uint32_t rx[16], ry[16];
    {
        int4 o[4], in[4];
        uint2 a[4];
#pragma unroll
        for (int j = 0; j < 4; j++) {
            int v = base / 4 + j * P1_THREADS + tid;
            if (v * 4 < T) {
                o[j]  = ld_stream4(reinterpret_cast<const int4*>(idx_out) + v);
                in[j] = ld_stream4(reinterpret_cast<const int4*>(idx_in) + v);
                a[j]  = ld_stream2(reinterpret_cast<const uint2*>(angle) + v);
            } else {
                o[j] = make_int4(-1, -1, -1, -1); in[j] = make_int4(0, 0, 0, 0); a[j] = make_uint2(0, 0);
            }
        }
        reinterpret_cast<uint4*>(s_off)[tid] = make_uint4(0, 0, 0, 0);
        __syncthreads();
#pragma unroll
        for (int j = 0; j < 4; j++) {
            const int ov[4] = {o[j].x, o[j].y, o[j].z, o[j].w};
            const int iv[4] = {in[j].x, in[j].y, in[j].z, in[j].w};
            const uint32_t av[4] = {a[j].x & 0xffffu, a[j].x >> 16, a[j].y & 0xffffu, a[j].y >> 16};
#pragma unroll
            for (int k = 0; k < 4; k++) {
                uint32_t bb = ((uint32_t)ov[k] >> EB_LOG) & 0xffffu;
                rx[j * 4 + k] = (uint32_t)iv[k] | ((uint32_t)(ov[k] & (EB - 1)) << IDX_BITS);
                ry[j * 4 + k] = av[k] | (bb << 16);
                if (ov[k] >= 0) atomicAdd(&s_off[bb], 1u);
            }
        }
    }
    __syncthreads();

    const int rep = blockIdx.x % NREP;
    uint2* const gq = g_q + (size_t)rep * CAPQ;
    const uint4 c = make_uint4(s_off[tid], s_off[tid + P1_THREADS], s_off[tid + 2 * P1_THREADS], s_off[tid + 3 * P1_THREADS]);
    const uint4 cp = make_uint4((c.x + 3u) & ~3u, (c.y + 3u) & ~3u, (c.z + 3u) & ~3u, (c.w + 3u) & ~3u);
    uint32_t* cnt = g_cnt + rep * NB_PAD + tid;
    uint32_t g0 = cp.x ? atomicAdd(cnt, cp.x) : 0u;
    uint32_t g1 = cp.y ? atomicAdd(cnt + P1_THREADS, cp.y) : 0u;
    uint32_t g2 = cp.z ? atomicAdd(cnt + 2 * P1_THREADS, cp.z) : 0u;
    uint32_t g3 = cp.w ? atomicAdd(cnt + 3 * P1_THREADS, cp.w) : 0u;
    uint32_t sum = cp.x + cp.y + cp.z + cp.w;
    uint32_t inc = sum;
#pragma unroll
    for (int d = 1; d < 32; d <<= 1) {
        uint32_t t = __shfl_up_sync(0xffffffffu, inc, d);
        if ((tid & 31) >= d) inc += t;
    }
    if ((tid & 31) == 31) s_warp[tid >> 5] = inc;
    __syncthreads();
    uint32_t wpre, total;
    {
        uint32_t x = ((tid & 31) < P1_THREADS / 32) ? s_warp[tid & 31] : 0u;
#pragma unroll
        for (int d = 1; d < P1_THREADS / 32; d <<= 1) {
            uint32_t t = __shfl_up_sync(0xffffffffu, x, d);
            if ((tid & 31) >= d) x += t;
        }
        total = __shfl_sync(0xffffffffu, x, P1_THREADS / 32 - 1);
        wpre = __shfl_sync(0xffffffffu, x, ((tid >> 5) + 31) & 31);
        if ((tid >> 5) == 0) wpre = 0;
    }
    uint32_t ex = wpre + inc - sum;
    const uint4 off = make_uint4(ex, ex + cp.x, ex + cp.x + cp.y, ex + cp.x + cp.y + cp.z);
    s_off[tid] = off.x; s_off[tid + P1_THREADS] = off.y; s_off[tid + 2 * P1_THREADS] = off.z; s_off[tid + 3 * P1_THREADS] = off.w;
    s_delta[tid] = (int)(g0 - off.x); s_delta[tid + P1_THREADS] = (int)(g1 - off.y);
    s_delta[tid + 2 * P1_THREADS] = (int)(g2 - off.z); s_delta[tid + 3 * P1_THREADS] = (int)(g3 - off.w);
    __syncthreads();

#pragma unroll
    for (int k = 0; k < 16; k++) {
        uint32_t b = ry[k] >> 16;
        if (b != 0xffffu) {
            uint32_t p = atomicAdd(&s_off[b], 1u);
            uint2 r = make_uint2(rx[k], ry[k]);
            if (p < (uint32_t)STAGE_CAP) stage[p] = r;
            else {
                uint32_t gp = p + s_delta[b];
                if (gp < (uint32_t)CAPQ) gq[(size_t)b * (NREP * CAPQ) + gp] = r;
            }
        }
    }
    __syncthreads();
#pragma unroll
    for (int k = 0; k < 4; k++) {
        const uint32_t b = tid + k * P1_THREADS;
        for (uint32_t p = s_off[b]; p & 3u; p++) {
            uint2 d = make_uint2(0xffffffffu, b << 16);
            if (p < (uint32_t)STAGE_CAP) stage[p] = d;
            else {
                uint32_t gp = p + s_delta[b];
                if (gp < (uint32_t)CAPQ) gq[(size_t)b * (NREP * CAPQ) + gp] = d;
            }
        }
    }
    __syncthreads();

    const int n = min((int)total, STAGE_CAP);
#pragma unroll 4
    for (int i = tid; i < n; i += P1_THREADS) {
        uint2 r = stage[i];
        uint32_t b = r.y >> 16;
        uint32_t p = (uint32_t)(i + s_delta[b]);
        if (p < (uint32_t)CAPQ) gq[(size_t)b * (NREP * CAPQ) + p] = r;
    }
}

__global__ void __launch_bounds__(P2_THREADS, 2)
edge_kernel(const uint16_t* __restrict__ m, const int* __restrict__ idx_in, const int* __restrict__ idx_out,
            const uint16_t* __restrict__ dist, const uint16_t* __restrict__ angle,
            const uint16_t* __restrict__ centers, const uint16_t* __restrict__ ang_freq,
            const uint16_t* __restrict__ w_rbf, const uint16_t* __restrict__ w_sbf,
            const uint16_t* __restrict__ w_down, const uint16_t* __restrict__ w_up,
            uint16_t* __restrict__ out, int E, int T)
{
    extern __shared__ __align__(16) uint4 srec[];
    __shared__ uint32_t s_start[EB + 1];
    __shared__ uint32_t s_wsum[EB / 32];
    __shared__ uint32_t s_n[NREP];

    const int tid  = threadIdx.x;
    const int lane = tid & 31;
    const int warp = tid >> 5;
    const int g    = lane >> 2;
    const int t    = lane & 3;
    const int b    = blockIdx.x;

    if (tid < NREP) { s_n[tid] = g_cnt[tid * NB_PAD + b]; g_cnt[tid * NB_PAD + b] = 0; }
    if (tid < EB) s_start[tid] = 0;
    const float f0 = bf16_bits_to_f(ang_freq[0]);
    const float f1 = bf16_bits_to_f(ang_freq[1]);
    const float f2 = bf16_bits_to_f(ang_freq[2]);
    __syncthreads();
    const uint32_t n0 = s_n[0], n1 = s_n[1], n2 = s_n[2], n3 = s_n[3];
    const uint32_t e1 = n0 + n1, e2 = e1 + n2, n = e2 + n3;

    float S[2][3][4];
#pragma unroll
    for (int h = 0; h < 2; h++)
#pragma unroll
        for (int l = 0; l < 3; l++)
#pragma unroll
            for (int j = 0; j < 4; j++) S[h][l][j] = 0.f;

    bool fast = n <= (uint32_t)CAPR && max(max(n0, n1), max(n2, n3)) <= (uint32_t)CAPQ;
    uint32_t w[P2_RPT], av[P2_RPT], rk[P2_RPT];
    if (fast) {
        const uint2* gq = g_q + (size_t)b * (NREP * CAPQ);
#pragma unroll
        for (int k = 0; k < P2_RPT / 2; k++) {
            uint32_t i = 2 * (tid + k * P2_THREADS);
            uint4 v = make_uint4(0xffffffffu, 0, 0xffffffffu, 0);
            uint32_t q = i < n0 ? i : i < e1 ? i - n0 + CAPQ : i < e2 ? i - e1 + 2 * CAPQ : i - e2 + 3 * CAPQ;
            if (i < n) v = __ldcs(reinterpret_cast<const uint4*>(gq + q));
            w[2 * k] = v.x; av[2 * k] = v.y & 0xffffu; w[2 * k + 1] = v.z; av[2 * k + 1] = v.w & 0xffffu;
        }
#pragma unroll
        for (int k = 0; k < P2_RPT; k++)
            if (w[k] != 0xffffffffu) rk[k] = atomicAdd(&s_start[w[k] >> IDX_BITS], 1u);
        __syncthreads();
        uint32_t cnt = 0, inc = 0;
        if (tid < EB) {
            cnt = s_start[tid];
            inc = cnt;
#pragma unroll
            for (int d = 1; d < 32; d <<= 1) {
                uint32_t x = __shfl_up_sync(0xffffffffu, inc, d);
                if (lane >= d) inc += x;
            }
            if (lane == 31) s_wsum[warp] = inc;
        }
        __syncthreads();
        if (tid < EB) {
            uint32_t pre = 0;
#pragma unroll
            for (int x = 0; x < EB / 32; x++) pre += (x < warp) ? s_wsum[x] : 0u;
            s_start[tid] = pre + inc - cnt;
            if (tid == EB - 1) s_start[EB] = pre + inc;
        }
        __syncthreads();
        fast = s_start[EB] <= (uint32_t)CAP;
    }
    if (fast) {
#pragma unroll
        for (int k = 0; k < P2_RPT; k++) {
            if (w[k] != 0xffffffffu) {
                uint32_t p = s_start[w[k] >> IDX_BITS] + rk[k];
                float an = bf16_bits_to_f(av[k]);
                srec[p] = make_uint4((w[k] & ((1u << IDX_BITS) - 1)) * 32u,
                                     __float_as_uint(cbf_val(f0, an)),
                                     __float_as_uint(cbf_val(f1, an)),
                                     __float_as_uint(cbf_val(f2, an)));
            }
        }
        __syncthreads();

        const char* mbase = reinterpret_cast<const char*>(m) + t * 8;
#pragma unroll
        for (int h = 0; h < 2; h++) {
            const int el = 16 * warp + 8 * h + g;
            const uint32_t s = s_start[el], en = s_start[el + 1];
            for (uint32_t i = s; i < en; i += 4) {
                uint4 r[4]; uint2 v[4];
#pragma unroll
                for (int u = 0; u < 4; u++) {
                    if (i + u < en) {
                        r[u] = srec[i + u];
                        v[u] = __ldg(reinterpret_cast<const uint2*>(mbase + r[u].x));
                    } else {
                        r[u] = make_uint4(0, 0, 0, 0); v[u] = make_uint2(0, 0);
                    }
                }
#pragma unroll
                for (int u = 0; u < 4; u++) {
                    float x0 = __uint_as_float(v[u].x << 16), x1 = __uint_as_float(v[u].x & 0xffff0000u);
                    float x2 = __uint_as_float(v[u].y << 16), x3 = __uint_as_float(v[u].y & 0xffff0000u);
                    float c0 = __uint_as_float(r[u].y), c1 = __uint_as_float(r[u].z), c2 = __uint_as_float(r[u].w);
                    S[h][0][0] = fmaf(c0, x0, S[h][0][0]); S[h][0][1] = fmaf(c0, x1, S[h][0][1]);
                    S[h][0][2] = fmaf(c0, x2, S[h][0][2]); S[h][0][3] = fmaf(c0, x3, S[h][0][3]);
                    S[h][1][0] = fmaf(c1, x0, S[h][1][0]); S[h][1][1] = fmaf(c1, x1, S[h][1][1]);
                    S[h][1][2] = fmaf(c1, x2, S[h][1][2]); S[h][1][3] = fmaf(c1, x3, S[h][1][3]);
                    S[h][2][0] = fmaf(c2, x0, S[h][2][0]); S[h][2][1] = fmaf(c2, x1, S[h][2][1]);
                    S[h][2][2] = fmaf(c2, x2, S[h][2][2]); S[h][2][3] = fmaf(c2, x3, S[h][2][3]);
                }
            }
        }
    } else {
        float* sacc = reinterpret_cast<float*>(srec);
        for (int i = tid; i < EB * 48; i += P2_THREADS) sacc[i] = 0.f;
        __syncthreads();
        for (int i = tid; i < T; i += P2_THREADS) {
            int o = idx_out[i];
            if ((o >> EB_LOG) == b) {
                float an = bf16_bits_to_f(angle[i]);
                float c[3] = {cbf_val(f0, an), cbf_val(f1, an), cbf_val(f2, an)};
                const uint16_t* row = m + (size_t)idx_in[i] * 16;
                float* dst = sacc + (o & (EB - 1)) * 48;
                for (int k = 0; k < 16; k++) {
                    float x = bf16_bits_to_f(row[k]);
                    atomicAdd(dst + k, c[0] * x);
                    atomicAdd(dst + 16 + k, c[1] * x);
                    atomicAdd(dst + 32 + k, c[2] * x);
                }
            }
        }
        __syncthreads();
#pragma unroll
        for (int h = 0; h < 2; h++) {
            const int el = 16 * warp + 8 * h + g;
#pragma unroll
            for (int l = 0; l < 3; l++)
#pragma unroll
                for (int j = 0; j < 4; j++) S[h][l][j] = sacc[el * 48 + l * 16 + 4 * t + j];
        }
    }

    const int eA = b * EB + 16 * warp + g;
    const int eB = eA + 8;
    const bool okA = eA < E, okB = eB < E;

    const float cA = bf16_bits_to_f(centers[2 * t]), cB = bf16_bits_to_f(centers[2 * t + 1]);
    const float dA = okA ? bf16_bits_to_f(dist[eA]) : 0.f;
    const float dB = okB ? bf16_bits_to_f(dist[eB]) : 0.f;
    const uint32_t ra0 = pack_bf16(rbf_val(dA, cA), rbf_val(dA, cB));
    const uint32_t ra1 = pack_bf16(rbf_val(dB, cA), rbf_val(dB, cB));

    auto ld2 = [](const uint16_t* p0, const uint16_t* p1) -> uint32_t {
        return (uint32_t)__ldg(p0) | ((uint32_t)__ldg(p1) << 16);
    };

    float y[3][2][4];
#pragma unroll
    for (int tl = 0; tl < 3; tl++)
#pragma unroll
        for (int j = 0; j < 2; j++)
#pragma unroll
            for (int i = 0; i < 4; i++) y[tl][j][i] = 0.f;
    {
        uint32_t wd[2][2];
#pragma unroll
        for (int j = 0; j < 2; j++) {
            wd[j][0] = ld2(w_down + (4 * t + 0) * 16 + 8 * j + g, w_down + (4 * t + 1) * 16 + 8 * j + g);
            wd[j][1] = ld2(w_down + (4 * t + 2) * 16 + 8 * j + g, w_down + (4 * t + 3) * 16 + 8 * j + g);
        }
#pragma unroll
        for (int tl = 0; tl < 3; tl++) {
            const float* P = (tl == 0) ? S[0][0] : (tl == 1) ? S[1][0] : S[0][2];
            const float* Q = (tl == 0) ? S[0][1] : (tl == 1) ? S[1][1] : S[1][2];
            uint32_t h0 = pack_bf16(P[0], P[1]), h1 = pack_bf16(Q[0], Q[1]);
            uint32_t h2 = pack_bf16(P[2], P[3]), h3 = pack_bf16(Q[2], Q[3]);
            uint32_t l0 = pack_bf16(P[0] - __uint_as_float(h0 << 16), P[1] - __uint_as_float(h0 & 0xffff0000u));
            uint32_t l1 = pack_bf16(Q[0] - __uint_as_float(h1 << 16), Q[1] - __uint_as_float(h1 & 0xffff0000u));
            uint32_t l2 = pack_bf16(P[2] - __uint_as_float(h2 << 16), P[3] - __uint_as_float(h2 & 0xffff0000u));
            uint32_t l3 = pack_bf16(Q[2] - __uint_as_float(h3 << 16), Q[3] - __uint_as_float(h3 & 0xffff0000u));
#pragma unroll
            for (int j = 0; j < 2; j++) {
                mma16816(y[tl][j], h0, h1, h2, h3, wd[j][0], wd[j][1]);
                mma16816(y[tl][j], l0, l1, l2, l3, wd[j][0], wd[j][1]);
            }
        }
    }
    float aggA[2][2] = {{0.f, 0.f}, {0.f, 0.f}}, aggB[2][2] = {{0.f, 0.f}, {0.f, 0.f}};
#pragma unroll
    for (int l = 0; l < 3; l++) {
#pragma unroll
        for (int j = 0; j < 2; j++) {
            uint32_t ws = ld2(w_sbf + (3 * (2 * t) + l) * 16 + 8 * j + g, w_sbf + (3 * (2 * t + 1) + l) * 16 + 8 * j + g);
            float G[4] = {0.f, 0.f, 0.f, 0.f};
            mma1688(G, ra0, ra1, ws);
            float ya0, ya1, yb0, yb1;
            if (l == 0)      { ya0 = y[0][j][0]; ya1 = y[0][j][1]; yb0 = y[1][j][0]; yb1 = y[1][j][1]; }
            else if (l == 1) { ya0 = y[0][j][2]; ya1 = y[0][j][3]; yb0 = y[1][j][2]; yb1 = y[1][j][3]; }
            else             { ya0 = y[2][j][0]; ya1 = y[2][j][1]; yb0 = y[2][j][2]; yb1 = y[2][j][3]; }
            aggA[j][0] = fmaf(ya0, G[0], aggA[j][0]); aggA[j][1] = fmaf(ya1, G[1], aggA[j][1]);
            aggB[j][0] = fmaf(yb0, G[2], aggB[j][0]); aggB[j][1] = fmaf(yb1, G[3], aggB[j][1]);
        }
    }
    float u[2][4], rw[2][4];
    {
        uint32_t h0 = pack_bf16(aggA[0][0], aggA[0][1]), h1 = pack_bf16(aggB[0][0], aggB[0][1]);
        uint32_t h2 = pack_bf16(aggA[1][0], aggA[1][1]), h3 = pack_bf16(aggB[1][0], aggB[1][1]);
        uint32_t l0 = pack_bf16(aggA[0][0] - __uint_as_float(h0 << 16), aggA[0][1] - __uint_as_float(h0 & 0xffff0000u));
        uint32_t l1 = pack_bf16(aggB[0][0] - __uint_as_float(h1 << 16), aggB[0][1] - __uint_as_float(h1 & 0xffff0000u));
        uint32_t l2 = pack_bf16(aggA[1][0] - __uint_as_float(h2 << 16), aggA[1][1] - __uint_as_float(h2 & 0xffff0000u));
        uint32_t l3 = pack_bf16(aggB[1][0] - __uint_as_float(h3 << 16), aggB[1][1] - __uint_as_float(h3 & 0xffff0000u));
#pragma unroll
        for (int j = 0; j < 2; j++) {
            const int col = 4 * (g >> 1) + 2 * j + (g & 1);
            uint32_t b0 = ld2(w_up + (2 * t) * 16 + col, w_up + (2 * t + 1) * 16 + col);
            uint32_t b1 = ld2(w_up + (2 * t + 8) * 16 + col, w_up + (2 * t + 9) * 16 + col);
            uint32_t br = ld2(w_rbf + (2 * t) * 16 + col, w_rbf + (2 * t + 1) * 16 + col);
#pragma unroll
            for (int i = 0; i < 4; i++) { u[j][i] = 0.f; rw[j][i] = 0.f; }
            mma16816(u[j], h0, h1, h2, h3, b0, b1);
            mma16816(u[j], l0, l1, l2, l3, b0, b1);
            mma1688(rw[j], ra0, ra1, br);
        }
    }
    if (okA) {
        uint2 mv = __ldg(reinterpret_cast<const uint2*>(m + (size_t)eA * 16 + 4 * t));
        float o0 = fmaf(u[0][0], rw[0][0], __uint_as_float(mv.x << 16));
        float o1 = fmaf(u[0][1], rw[0][1], __uint_as_float(mv.x & 0xffff0000u));
        float o2 = fmaf(u[1][0], rw[1][0], __uint_as_float(mv.y << 16));
        float o3 = fmaf(u[1][1], rw[1][1], __uint_as_float(mv.y & 0xffff0000u));
        *reinterpret_cast<uint2*>(out + (size_t)eA * 16 + 4 * t) = make_uint2(pack_bf16(o0, o1), pack_bf16(o2, o3));
    }
    if (okB) {
        uint2 mv = __ldg(reinterpret_cast<const uint2*>(m + (size_t)eB * 16 + 4 * t));
        float o0 = fmaf(u[0][2], rw[0][2], __uint_as_float(mv.x << 16));
        float o1 = fmaf(u[0][3], rw[0][3], __uint_as_float(mv.x & 0xffff0000u));
        float o2 = fmaf(u[1][2], rw[1][2], __uint_as_float(mv.y << 16));
        float o3 = fmaf(u[1][3], rw[1][3], __uint_as_float(mv.y & 0xffff0000u));
        *reinterpret_cast<uint2*>(out + (size_t)eB * 16 + 4 * t) = make_uint2(pack_bf16(o0, o1), pack_bf16(o2, o3));
    }
}

}

extern "C" void kernel_launch(void* const* d_in, const int* in_sizes, int n_in,
                              void* d_out, int out_size) {
    const uint16_t* m        = (const uint16_t*)d_in[0];
    const int*      idx_in   = (const int*)d_in[1];
    const int*      idx_out  = (const int*)d_in[2];
    const uint16_t* dist     = (const uint16_t*)d_in[3];
    const uint16_t* angle    = (const uint16_t*)d_in[4];
    const uint16_t* centers  = (const uint16_t*)d_in[5];
    const uint16_t* ang_freq = (const uint16_t*)d_in[6];
    const uint16_t* w_rbf    = (const uint16_t*)d_in[7];
    const uint16_t* w_sbf    = (const uint16_t*)d_in[8];
    const uint16_t* w_down   = (const uint16_t*)d_in[9];
    const uint16_t* w_up     = (const uint16_t*)d_in[10];
    uint16_t* out = (uint16_t*)d_out;
    const int E = in_sizes[3];
    const int T = in_sizes[1];

    static bool init = false;
    if (!init) {
        cudaFuncSetAttribute(part_kernel, cudaFuncAttributeMaxDynamicSharedMemorySize, STAGE_CAP * 8);
        cudaFuncSetAttribute(edge_kernel, cudaFuncAttributeMaxDynamicSharedMemorySize, CAP * 16);
        init = true;
    }
    const int nb = (E + EB - 1) / EB;
    part_kernel<<<(T + C1 - 1) / C1, P1_THREADS, STAGE_CAP * 8>>>(idx_in, idx_out, angle, T);
    edge_kernel<<<nb, P2_THREADS, CAP * 16>>>(m, idx_in, idx_out, dist, angle, centers, ang_freq,
                                              w_rbf, w_sbf, w_down, w_up, out, E, T);
}
```

```cpp
#include <cuda_runtime.h>
#include <cuda_bf16.h>
#include <stdint.h>

namespace {

constexpr int kMaxE   = 400000;
constexpr int IDX_BITS = 19;
constexpr int EB_LOG  = 8;
constexpr int EB      = 1 << EB_LOG;
constexpr int NB_MAX  = (kMaxE + EB - 1) / EB;
constexpr int NB_PAD  = 2048;
constexpr int CAP     = 4608;
constexpr int CAPR    = 6144;
constexpr int NREP    = 4;
constexpr int CAPQ    = 1664;
constexpr int STAGE_CAP = 11264;

constexpr int P1_THREADS = 512;
constexpr int P1_RPT     = 16;
constexpr int C1         = P1_THREADS * P1_RPT;

constexpr int P2_THREADS = 512;
constexpr int P2_RPT     = CAPR / P2_THREADS;

__device__ uint32_t g_cnt[NREP * NB_PAD];
__device__ __align__(128) uint2 g_q[(size_t)NB_MAX * NREP * CAPQ];

__device__ __forceinline__ int4 ld_stream4(const int4* p) { return __ldcs(p); }
__device__ __forceinline__ uint2 ld_stream2(const uint2* p) { return __ldcs(p); }

__device__ __forceinline__ float bf16r(float x) { return __bfloat162float(__float2bfloat16_rn(x)); }
__device__ __forceinline__ float bf16_bits_to_f(uint32_t h) { return __uint_as_float(h << 16); }
__device__ __forceinline__ uint32_t pack_bf16(float lo, float hi) {
    __nv_bfloat162 v = __floats2bfloat162_rn(lo, hi);
    return *reinterpret_cast<uint32_t*>(&v);
}

__device__ __noinline__ float cos_slow(float x) { return cosf(x); }
__device__ __forceinline__ float cos_acc(float x) {
    if (fabsf(x) > 1000.f) return cos_slow(x);
    float k = rintf(x * 0.15915494309189535f);
    float r = fmaf(k, -6.28318548202514648f, x);
    r = fmaf(k, 1.7484555314695172e-7f, r);
    return __cosf(r);
}
__device__ __forceinline__ float cbf_val(float freq, float ang) {
    return bf16r(cos_acc(bf16r(freq * ang)));
}
__device__ __forceinline__ float rbf_val(float d, float c) {
    float x = bf16r(d - c);
    float s = bf16r(x * x);
    float a = bf16r(-10.f * s);
    return bf16r(expf(a));
}

__device__ __forceinline__ void mma16816(float* d, uint32_t a0, uint32_t a1, uint32_t a2, uint32_t a3,
                                         uint32_t b0, uint32_t b1) {
    asm volatile("mma.sync.aligned.m16n8k16.row.col.f32.bf16.bf16.f32 {%0,%1,%2,%3}, {%4,%5,%6,%7}, {%8,%9}, {%0,%1,%2,%3};"
                 : "+f"(d[0]), "+f"(d[1]), "+f"(d[2]), "+f"(d[3])
                 : "r"(a0), "r"(a1), "r"(a2), "r"(a3), "r"(b0), "r"(b1));
}
__device__ __forceinline__ void mma1688(float* d, uint32_t a0, uint32_t a1, uint32_t b0) {
    asm volatile("mma.sync.aligned.m16n8k8.row.col.f32.bf16.bf16.f32 {%0,%1,%2,%3}, {%4,%5}, {%6}, {%0,%1,%2,%3};"
                 : "+f"(d[0]), "+f"(d[1]), "+f"(d[2]), "+f"(d[3])
                 : "r"(a0), "r"(a1), "r"(b0));
}

__global__ void __launch_bounds__(P1_THREADS, 2)
part_kernel(const int* __restrict__ idx_in, const int* __restrict__ idx_out,
            const uint16_t* __restrict__ angle, int T, int nchunks)
{
    extern __shared__ __align__(16) uint2 stage[];
    __shared__ __align__(16) uint32_t s_off[NB_PAD];
    __shared__ __align__(16) int      s_delta[NB_PAD];
    __shared__ uint32_t s_warp[P1_THREADS / 32];

    const int tid = threadIdx.x;
    const int rep = blockIdx.x % NREP;
    uint2* const gq = g_q + (size_t)rep * CAPQ;

    int4 o[4], in[4];
    uint2 a[4];
    auto load_chunk = [&](int chunk) {
#pragma unroll
        for (int j = 0; j < 4; j++) {
            int v = chunk * (C1 / 4) + j * P1_THREADS + tid;
            if (v * 4 < T) {
                o[j]  = ld_stream4(reinterpret_cast<const int4*>(idx_out) + v);
                in[j] = ld_stream4(reinterpret_cast<const int4*>(idx_in) + v);
                a[j]  = ld_stream2(reinterpret_cast<const uint2*>(angle) + v);
            } else {
                o[j] = make_int4(-1, -1, -1, -1); in[j] = make_int4(0, 0, 0, 0); a[j] = make_uint2(0, 0);
            }
        }
    };
    load_chunk(blockIdx.x);

    for (int chunk = blockIdx.x; chunk < nchunks; chunk += gridDim.x) {
        reinterpret_cast<uint4*>(s_off)[tid] = make_uint4(0, 0, 0, 0);
        __syncthreads();
        uint32_t rx[16], ry[16];
#pragma unroll
        for (int j = 0; j < 4; j++) {
            const int ov[4] = {o[j].x, o[j].y, o[j].z, o[j].w};
            const int iv[4] = {in[j].x, in[j].y, in[j].z, in[j].w};
            const uint32_t av[4] = {a[j].x & 0xffffu, a[j].x >> 16, a[j].y & 0xffffu, a[j].y >> 16};
#pragma unroll
            for (int k = 0; k < 4; k++) {
                uint32_t bb = ((uint32_t)ov[k] >> EB_LOG) & 0xffffu;
                rx[j * 4 + k] = (uint32_t)iv[k] | ((uint32_t)(ov[k] & (EB - 1)) << IDX_BITS);
                ry[j * 4 + k] = av[k] | (bb << 16);
                if (ov[k] >= 0) atomicAdd(&s_off[bb], 1u);
            }
        }
        __syncthreads();

        const uint4 c = make_uint4(s_off[tid], s_off[tid + P1_THREADS], s_off[tid + 2 * P1_THREADS], s_off[tid + 3 * P1_THREADS]);
        const uint4 cp = make_uint4((c.x + 3u) & ~3u, (c.y + 3u) & ~3u, (c.z + 3u) & ~3u, (c.w + 3u) & ~3u);
        uint32_t* cnt = g_cnt + rep * NB_PAD + tid;
        uint32_t g0 = cp.x ? atomicAdd(cnt, cp.x) : 0u;
        uint32_t g1 = cp.y ? atomicAdd(cnt + P1_THREADS, cp.y) : 0u;
        uint32_t g2 = cp.z ? atomicAdd(cnt + 2 * P1_THREADS, cp.z) : 0u;
        uint32_t g3 = cp.w ? atomicAdd(cnt + 3 * P1_THREADS, cp.w) : 0u;
        uint32_t sum = cp.x + cp.y + cp.z + cp.w;
        uint32_t inc = sum;
#pragma unroll
        for (int d = 1; d < 32; d <<= 1) {
            uint32_t t = __shfl_up_sync(0xffffffffu, inc, d);
            if ((tid & 31) >= d) inc += t;
        }
        if ((tid & 31) == 31) s_warp[tid >> 5] = inc;
        __syncthreads();
        uint32_t wpre, total;
        {
            uint32_t x = ((tid & 31) < P1_THREADS / 32) ? s_warp[tid & 31] : 0u;
#pragma unroll
            for (int d = 1; d < P1_THREADS / 32; d <<= 1) {
                uint32_t t = __shfl_up_sync(0xffffffffu, x, d);
                if ((tid & 31) >= d) x += t;
            }
            total = __shfl_sync(0xffffffffu, x, P1_THREADS / 32 - 1);
            wpre = __shfl_sync(0xffffffffu, x, ((tid >> 5) + 31) & 31);
            if ((tid >> 5) == 0) wpre = 0;
        }
        const uint32_t ex = wpre + inc - sum;
        s_off[tid] = ex; s_off[tid + P1_THREADS] = ex + cp.x;
        s_off[tid + 2 * P1_THREADS] = ex + cp.x + cp.y; s_off[tid + 3 * P1_THREADS] = ex + cp.x + cp.y + cp.z;
        const bool spill = total > (uint32_t)STAGE_CAP;
        if (spill) {
            s_delta[tid] = (int)(g0 - ex); s_delta[tid + P1_THREADS] = (int)(g1 - (ex + cp.x));
            s_delta[tid + 2 * P1_THREADS] = (int)(g2 - (ex + cp.x + cp.y));
            s_delta[tid + 3 * P1_THREADS] = (int)(g3 - (ex + cp.x + cp.y + cp.z));
        }
        __syncthreads();

#pragma unroll
        for (int k = 0; k < 16; k++) {
            uint32_t b = ry[k] >> 16;
            if (b != 0xffffu) {
                uint32_t p = atomicAdd(&s_off[b], 1u);
                uint2 r = make_uint2(rx[k], ry[k]);
                if (p < (uint32_t)STAGE_CAP) stage[p] = r;
                else {
                    uint32_t gp = p + s_delta[b];
                    if (gp < (uint32_t)CAPQ) gq[(size_t)b * (NREP * CAPQ) + gp] = r;
                }
            }
        }
        if (!spill) {
            s_delta[tid] = (int)(g0 - ex); s_delta[tid + P1_THREADS] = (int)(g1 - (ex + cp.x));
            s_delta[tid + 2 * P1_THREADS] = (int)(g2 - (ex + cp.x + cp.y));
            s_delta[tid + 3 * P1_THREADS] = (int)(g3 - (ex + cp.x + cp.y + cp.z));
        }
        if (chunk + (int)gridDim.x < nchunks) load_chunk(chunk + gridDim.x);
        __syncthreads();
#pragma unroll
        for (int k = 0; k < 4; k++) {
            const uint32_t b = tid + k * P1_THREADS;
            for (uint32_t p = s_off[b]; p & 3u; p++) {
                uint2 d = make_uint2(0xffffffffu, b << 16);
                if (p < (uint32_t)STAGE_CAP) stage[p] = d;
                else {
                    uint32_t gp = p + s_delta[b];
                    if (gp < (uint32_t)CAPQ) gq[(size_t)b * (NREP * CAPQ) + gp] = d;
                }
            }
        }
        __syncthreads();

        const int n2 = min((int)total, STAGE_CAP) / 2;
#pragma unroll 4
        for (int i = tid; i < n2; i += P1_THREADS) {
            uint4 r = reinterpret_cast<const uint4*>(stage)[i];
            uint32_t b = r.y >> 16;
            uint32_t p = (uint32_t)(2 * i + s_delta[b]);
            if (p < (uint32_t)CAPQ) *reinterpret_cast<uint4*>(gq + (size_t)b * (NREP * CAPQ) + p) = r;
        }
        __syncthreads();
    }
}

__global__ void __launch_bounds__(P2_THREADS, 2)
edge_kernel(const uint16_t* __restrict__ m, const int* __restrict__ idx_in, const int* __restrict__ idx_out,
            const uint16_t* __restrict__ dist, const uint16_t* __restrict__ angle,
            const uint16_t* __restrict__ centers, const uint16_t* __restrict__ ang_freq,
            const uint16_t* __restrict__ w_rbf, const uint16_t* __restrict__ w_sbf,
            const uint16_t* __restrict__ w_down, const uint16_t* __restrict__ w_up,
            uint16_t* __restrict__ out, int E, int T)
{
    extern __shared__ __align__(16) uint4 srec[];
    __shared__ uint32_t s_start[EB + 1];
    __shared__ uint32_t s_wsum[EB / 32];
    __shared__ uint32_t s_n[NREP];

    const int tid  = threadIdx.x;
    const int lane = tid & 31;
    const int warp = tid >> 5;
    const int g    = lane >> 2;
    const int t    = lane & 3;
    const int b    = blockIdx.x;

    if (tid < NREP) { s_n[tid] = g_cnt[tid * NB_PAD + b]; g_cnt[tid * NB_PAD + b] = 0; }
    if (tid < EB) s_start[tid] = 0;
    const float f0 = bf16_bits_to_f(ang_freq[0]);
    const float f1 = bf16_bits_to_f(ang_freq[1]);
    const float f2 = bf16_bits_to_f(ang_freq[2]);
    __syncthreads();
    const uint32_t n0 = s_n[0], n1 = s_n[1], n2 = s_n[2], n3 = s_n[3];
    const uint32_t e1 = n0 + n1, e2 = e1 + n2, n = e2 + n3;

    float S[2][3][4];
#pragma unroll
    for (int h = 0; h < 2; h++)
#pragma unroll
        for (int l = 0; l < 3; l++)
#pragma unroll
            for (int j = 0; j < 4; j++) S[h][l][j] = 0.f;

    bool fast = n <= (uint32_t)CAPR && max(max(n0, n1), max(n2, n3)) <= (uint32_t)CAPQ;
    uint32_t w[P2_RPT], av[P2_RPT], rk[P2_RPT];
    if (fast) {
        const uint2* gq = g_q + (size_t)b * (NREP * CAPQ);
#pragma unroll
        for (int k = 0; k < P2_RPT / 2; k++) {
            uint32_t i = 2 * (tid + k * P2_THREADS);
            uint4 v = make_uint4(0xffffffffu, 0, 0xffffffffu, 0);
            uint32_t q = i < n0 ? i : i < e1 ? i - n0 + CAPQ : i < e2 ? i - e1 + 2 * CAPQ : i - e2 + 3 * CAPQ;
            if (i < n) v = __ldcs(reinterpret_cast<const uint4*>(gq + q));
            w[2 * k] = v.x; av[2 * k] = v.y & 0xffffu; w[2 * k + 1] = v.z; av[2 * k + 1] = v.w & 0xffffu;
        }
#pragma unroll
        for (int k = 0; k < P2_RPT; k++)
            if (w[k] != 0xffffffffu) rk[k] = atomicAdd(&s_start[w[k] >> IDX_BITS], 1u);
        __syncthreads();
        uint32_t cnt = 0, inc = 0;
        if (tid < EB) {
            cnt = s_start[tid];
            inc = cnt;
#pragma unroll
            for (int d = 1; d < 32; d <<= 1) {
                uint32_t x = __shfl_up_sync(0xffffffffu, inc, d);
                if (lane >= d) inc += x;
            }
            if (lane == 31) s_wsum[warp] = inc;
        }
        __syncthreads();
        if (tid < EB) {
            uint32_t pre = 0;
#pragma unroll
            for (int x = 0; x < EB / 32; x++) pre += (x < warp) ? s_wsum[x] : 0u;
            s_start[tid] = pre + inc - cnt;
            if (tid == EB - 1) s_start[EB] = pre + inc;
        }
        __syncthreads();
        fast = s_start[EB] <= (uint32_t)CAP;
    }
    if (fast) {
#pragma unroll
        for (int k = 0; k < P2_RPT; k++) {
            if (w[k] != 0xffffffffu) {
                uint32_t p = s_start[w[k] >> IDX_BITS] + rk[k];
                float an = bf16_bits_to_f(av[k]);
                srec[p] = make_uint4((w[k] & ((1u << IDX_BITS) - 1)) * 32u,
                                     __float_as_uint(cbf_val(f0, an)),
                                     __float_as_uint(cbf_val(f1, an)),
                                     __float_as_uint(cbf_val(f2, an)));
            }
        }
        __syncthreads();

        const char* mbase = reinterpret_cast<const char*>(m) + t * 8;
#pragma unroll
        for (int h = 0; h < 2; h++) {
            const int el = 16 * warp + 8 * h + g;
            const uint32_t s = s_start[el], en = s_start[el + 1];
            for (uint32_t i = s; i < en; i += 4) {
                uint4 r[4]; uint2 v[4];
#pragma unroll
                for (int u = 0; u < 4; u++) {
                    if (i + u < en) {
                        r[u] = srec[i + u];
                        v[u] = __ldg(reinterpret_cast<const uint2*>(mbase + r[u].x));
                    } else {
                        r[u] = make_uint4(0, 0, 0, 0); v[u] = make_uint2(0, 0);
                    }
                }
#pragma unroll
                for (int u = 0; u < 4; u++) {
                    float x0 = __uint_as_float(v[u].x << 16), x1 = __uint_as_float(v[u].x & 0xffff0000u);
                    float x2 = __uint_as_float(v[u].y << 16), x3 = __uint_as_float(v[u].y & 0xffff0000u);
                    float c0 = __uint_as_float(r[u].y), c1 = __uint_as_float(r[u].z), c2 = __uint_as_float(r[u].w);
                    S[h][0][0] = fmaf(c0, x0, S[h][0][0]); S[h][0][1] = fmaf(c0, x1, S[h][0][1]);
                    S[h][0][2] = fmaf(c0, x2, S[h][0][2]); S[h][0][3] = fmaf(c0, x3, S[h][0][3]);
                    S[h][1][0] = fmaf(c1, x0, S[h][1][0]); S[h][1][1] = fmaf(c1, x1, S[h][1][1]);
                    S[h][1][2] = fmaf(c1, x2, S[h][1][2]); S[h][1][3] = fmaf(c1, x3, S[h][1][3]);
                    S[h][2][0] = fmaf(c2, x0, S[h][2][0]); S[h][2][1] = fmaf(c2, x1, S[h][2][1]);
                    S[h][2][2] = fmaf(c2, x2, S[h][2][2]); S[h][2][3] = fmaf(c2, x3, S[h][2][3]);
                }
            }
        }
    } else {
        float* sacc = reinterpret_cast<float*>(srec);
        for (int i = tid; i < EB * 48; i += P2_THREADS) sacc[i] = 0.f;
        __syncthreads();
        for (int i = tid; i < T; i += P2_THREADS) {
            int o = idx_out[i];
            if ((o >> EB_LOG) == b) {
                float an = bf16_bits_to_f(angle[i]);
                float c[3] = {cbf_val(f0, an), cbf_val(f1, an), cbf_val(f2, an)};
                const uint16_t* row = m + (size_t)idx_in[i] * 16;
                float* dst = sacc + (o & (EB - 1)) * 48;
                for (int k = 0; k < 16; k++) {
                    float x = bf16_bits_to_f(row[k]);
                    atomicAdd(dst + k, c[0] * x);
                    atomicAdd(dst + 16 + k, c[1] * x);
                    atomicAdd(dst + 32 + k, c[2] * x);
                }
            }
        }
        __syncthreads();
#pragma unroll
        for (int h = 0; h < 2; h++) {
            const int el = 16 * warp + 8 * h + g;
#pragma unroll
            for (int l = 0; l < 3; l++)
#pragma unroll
                for (int j = 0; j < 4; j++) S[h][l][j] = sacc[el * 48 + l * 16 + 4 * t + j];
        }
    }

    const int eA = b * EB + 16 * warp + g;
    const int eB = eA + 8;
    const bool okA = eA < E, okB = eB < E;

    const float cA = bf16_bits_to_f(centers[2 * t]), cB = bf16_bits_to_f(centers[2 * t + 1]);
    const float dA = okA ? bf16_bits_to_f(dist[eA]) : 0.f;
    const float dB = okB ? bf16_bits_to_f(dist[eB]) : 0.f;
    const uint32_t ra0 = pack_bf16(rbf_val(dA, cA), rbf_val(dA, cB));
    const uint32_t ra1 = pack_bf16(rbf_val(dB, cA), rbf_val(dB, cB));

    auto ld2 = [](const uint16_t* p0, const uint16_t* p1) -> uint32_t {
        return (uint32_t)__ldg(p0) | ((uint32_t)__ldg(p1) << 16);
    };

    float y[3][2][4];
#pragma unroll
    for (int tl = 0; tl < 3; tl++)
#pragma unroll
        for (int j = 0; j < 2; j++)
#pragma unroll
            for (int i = 0; i < 4; i++) y[tl][j][i] = 0.f;
    {
        uint32_t wd[2][2];
#pragma unroll
        for (int j = 0; j < 2; j++) {
            wd[j][0] = ld2(w_down + (4 * t + 0) * 16 + 8 * j + g, w_down + (4 * t + 1) * 16 + 8 * j + g);
            wd[j][1] = ld2(w_down + (4 * t + 2) * 16 + 8 * j + g, w_down + (4 * t + 3) * 16 + 8 * j + g);
        }
#pragma unroll
        for (int tl = 0; tl < 3; tl++) {
            const float* P = (tl == 0) ? S[0][0] : (tl == 1) ? S[1][0] : S[0][2];
            const float* Q = (tl == 0) ? S[0][1] : (tl == 1) ? S[1][1] : S[1][2];
            uint32_t h0 = pack_bf16(P[0], P[1]), h1 = pack_bf16(Q[0], Q[1]);
            uint32_t h2 = pack_bf16(P[2], P[3]), h3 = pack_bf16(Q[2], Q[3]);
            uint32_t l0 = pack_bf16(P[0] - __uint_as_float(h0 << 16), P[1] - __uint_as_float(h0 & 0xffff0000u));
            uint32_t l1 = pack_bf16(Q[0] - __uint_as_float(h1 << 16), Q[1] - __uint_as_float(h1 & 0xffff0000u));
            uint32_t l2 = pack_bf16(P[2] - __uint_as_float(h2 << 16), P[3] - __uint_as_float(h2 & 0xffff0000u));
            uint32_t l3 = pack_bf16(Q[2] - __uint_as_float(h3 << 16), Q[3] - __uint_as_float(h3 & 0xffff0000u));
#pragma unroll
            for (int j = 0; j < 2; j++) {
                mma16816(y[tl][j], h0, h1, h2, h3, wd[j][0], wd[j][1]);
                mma16816(y[tl][j], l0, l1, l2, l3, wd[j][0], wd[j][1]);
            }
        }
    }
    float aggA[2][2] = {{0.f, 0.f}, {0.f, 0.f}}, aggB[2][2] = {{0.f, 0.f}, {0.f, 0.f}};
#pragma unroll
    for (int l = 0; l < 3; l++) {
#pragma unroll
        for (int j = 0; j < 2; j++) {
            uint32_t ws = ld2(w_sbf + (3 * (2 * t) + l) * 16 + 8 * j + g, w_sbf + (3 * (2 * t + 1) + l) * 16 + 8 * j + g);
            float G[4] = {0.f, 0.f, 0.f, 0.f};
            mma1688(G, ra0, ra1, ws);
            float ya0, ya1, yb0, yb1;
            if (l == 0)      { ya0 = y[0][j][0]; ya1 = y[0][j][1]; yb0 = y[1][j][0]; yb1 = y[1][j][1]; }
            else if (l == 1) { ya0 = y[0][j][2]; ya1 = y[0][j][3]; yb0 = y[1][j][2]; yb1 = y[1][j][3]; }
            else             { ya0 = y[2][j][0]; ya1 = y[2][j][1]; yb0 = y[2][j][2]; yb1 = y[2][j][3]; }
            aggA[j][0] = fmaf(ya0, G[0], aggA[j][0]); aggA[j][1] = fmaf(ya1, G[1], aggA[j][1]);
            aggB[j][0] = fmaf(yb0, G[2], aggB[j][0]); aggB[j][1] = fmaf(yb1, G[3], aggB[j][1]);
        }
    }
    float u[2][4], rw[2][4];
    {
        uint32_t h0 = pack_bf16(aggA[0][0], aggA[0][1]), h1 = pack_bf16(aggB[0][0], aggB[0][1]);
        uint32_t h2 = pack_bf16(aggA[1][0], aggA[1][1]), h3 = pack_bf16(aggB[1][0], aggB[1][1]);
        uint32_t l0 = pack_bf16(aggA[0][0] - __uint_as_float(h0 << 16), aggA[0][1] - __uint_as_float(h0 & 0xffff0000u));
        uint32_t l1 = pack_bf16(aggB[0][0] - __uint_as_float(h1 << 16), aggB[0][1] - __uint_as_float(h1 & 0xffff0000u));
        uint32_t l2 = pack_bf16(aggA[1][0] - __uint_as_float(h2 << 16), aggA[1][1] - __uint_as_float(h2 & 0xffff0000u));
        uint32_t l3 = pack_bf16(aggB[1][0] - __uint_as_float(h3 << 16), aggB[1][1] - __uint_as_float(h3 & 0xffff0000u));
#pragma unroll
        for (int j = 0; j < 2; j++) {
            const int col = 4 * (g >> 1) + 2 * j + (g & 1);
            uint32_t b0 = ld2(w_up + (2 * t) * 16 + col, w_up + (2 * t + 1) * 16 + col);
            uint32_t b1 = ld2(w_up + (2 * t + 8) * 16 + col, w_up + (2 * t + 9) * 16 + col);
            uint32_t br = ld2(w_rbf + (2 * t) * 16 + col, w_rbf + (2 * t + 1) * 16 + col);
#pragma unroll
            for (int i = 0; i < 4; i++) { u[j][i] = 0.f; rw[j][i] = 0.f; }
            mma16816(u[j], h0, h1, h2, h3, b0, b1);
            mma16816(u[j], l0, l1, l2, l3, b0, b1);
            mma1688(rw[j], ra0, ra1, br);
        }
    }
    if (okA) {
        uint2 mv = __ldg(reinterpret_cast<const uint2*>(m + (size_t)eA * 16 + 4 * t));
        float o0 = fmaf(u[0][0], rw[0][0], __uint_as_float(mv.x << 16));
        float o1 = fmaf(u[0][1], rw[0][1], __uint_as_float(mv.x & 0xffff0000u));
        float o2 = fmaf(u[1][0], rw[1][0], __uint_as_float(mv.y << 16));
        float o3 = fmaf(u[1][1], rw[1][1], __uint_as_float(mv.y & 0xffff0000u));
        *reinterpret_cast<uint2*>(out + (size_t)eA * 16 + 4 * t) = make_uint2(pack_bf16(o0, o1), pack_bf16(o2, o3));
    }
    if (okB) {
        uint2 mv = __ldg(reinterpret_cast<const uint2*>(m + (size_t)eB * 16 + 4 * t));
        float o0 = fmaf(u[0][2], rw[0][2], __uint_as_float(mv.x << 16));
        float o1 = fmaf(u[0][3], rw[0][3], __uint_as_float(mv.x & 0xffff0000u));
        float o2 = fmaf(u[1][2], rw[1][2], __uint_as_float(mv.y << 16));
        float o3 = fmaf(u[1][3], rw[1][3], __uint_as_float(mv.y & 0xffff0000u));
        *reinterpret_cast<uint2*>(out + (size_t)eB * 16 + 4 * t) = make_uint2(pack_bf16(o0, o1), pack_bf16(o2, o3));
    }
}

}

extern "C" void kernel_launch(void* const* d_in, const int* in_sizes, int n_in,
                              void* d_out, int out_size) {
    const uint16_t* m        = (const uint16_t*)d_in[0];
    const int*      idx_in   = (const int*)d_in[1];
    const int*      idx_out  = (const int*)d_in[2];
    const uint16_t* dist     = (const uint16_t*)d_in[3];
    const uint16_t* angle    = (const uint16_t*)d_in[4];
    const uint16_t* centers  = (const uint16_t*)d_in[5];
    const uint16_t* ang_freq = (const uint16_t*)d_in[6];
    const uint16_t* w_rbf    = (const uint16_t*)d_in[7];
    const uint16_t* w_sbf    = (const uint16_t*)d_in[8];
    const uint16_t* w_down   = (const uint16_t*)d_in[9];
    const uint16_t* w_up     = (const uint16_t*)d_in[10];
    uint16_t* out = (uint16_t*)d_out;
    const int E = in_sizes[3];
    const int T = in_sizes[1];

    static bool init = false;
    if (!init) {
        cudaFuncSetAttribute(part_kernel, cudaFuncAttributeMaxDynamicSharedMemorySize, STAGE_CAP * 8);
        cudaFuncSetAttribute(edge_kernel, cudaFuncAttributeMaxDynamicSharedMemorySize, CAP * 16);
        init = true;
    }
    const int nb = (E + EB - 1) / EB;
    const int nchunks = (T + C1 - 1) / C1;
    part_kernel<<<min(nchunks, 264), P1_THREADS, STAGE_CAP * 8>>>(idx_in, idx_out, angle, T, nchunks);
    edge_kernel<<<nb, P2_THREADS, CAP * 16>>>(m, idx_in, idx_out, dist, angle, centers, ang_freq,
                                              w_rbf, w_sbf, w_down, w_up, out, E, T);
}
```

```cpp
#include <cuda_runtime.h>
#include <cuda_bf16.h>
#include <stdint.h>

namespace {

constexpr int kMaxE   = 400000;
constexpr int IDX_BITS = 19;
constexpr int EB_LOG  = 8;
constexpr int EB      = 1 << EB_LOG;
constexpr int NB_MAX  = (kMaxE + EB - 1) / EB;
constexpr int NB_PAD  = 2048;
constexpr int CAP     = 4608;
constexpr int CAPR    = 6144;
constexpr int NREP    = 4;
constexpr int CAPQ    = 1664;
constexpr int STAGE_CAP = 11264;

constexpr int P1_THREADS = 512;
constexpr int P1_RPT     = 16;
constexpr int C1         = P1_THREADS * P1_RPT;

constexpr int P2_THREADS = 512;
constexpr int P2_RPT     = CAPR / P2_THREADS;

__device__ uint32_t g_cnt[NREP * NB_PAD];
__device__ __align__(128) uint2 g_q[(size_t)NB_MAX * NREP * CAPQ];

__device__ __forceinline__ int4 ld_stream4(const int4* p) { return __ldcs(p); }
__device__ __forceinline__ uint2 ld_stream2(const uint2* p) { return __ldcs(p); }

__device__ __forceinline__ float bf16r(float x) { return __bfloat162float(__float2bfloat16_rn(x)); }
__device__ __forceinline__ float bf16_bits_to_f(uint32_t h) { return __uint_as_float(h << 16); }
__device__ __forceinline__ uint32_t pack_bf16(float lo, float hi) {
    __nv_bfloat162 v = __floats2bfloat162_rn(lo, hi);
    return *reinterpret_cast<uint32_t*>(&v);
}

__device__ __noinline__ float cos_slow(float x) { return cosf(x); }
__device__ __forceinline__ float cos_acc(float x) {
    if (fabsf(x) > 1000.f) return cos_slow(x);
    float k = rintf(x * 0.15915494309189535f);
    float r = fmaf(k, -6.28318548202514648f, x);
    r = fmaf(k, 1.7484555314695172e-7f, r);
    return __cosf(r);
}
__device__ __forceinline__ float cbf_val(float freq, float ang) {
    return bf16r(cos_acc(bf16r(freq * ang)));
}
__device__ __forceinline__ float rbf_val(float d, float c) {
    float x = bf16r(d - c);
    float s = bf16r(x * x);
    float a = bf16r(-10.f * s);
    return bf16r(expf(a));
}

__device__ __forceinline__ void mma16816(float* d, uint32_t a0, uint32_t a1, uint32_t a2, uint32_t a3,
                                         uint32_t b0, uint32_t b1) {
    asm volatile("mma.sync.aligned.m16n8k16.row.col.f32.bf16.bf16.f32 {%0,%1,%2,%3}, {%4,%5,%6,%7}, {%8,%9}, {%0,%1,%2,%3};"
                 : "+f"(d[0]), "+f"(d[1]), "+f"(d[2]), "+f"(d[3])
                 : "r"(a0), "r"(a1), "r"(a2), "r"(a3), "r"(b0), "r"(b1));
}
__device__ __forceinline__ void mma1688(float* d, uint32_t a0, uint32_t a1, uint32_t b0) {
    asm volatile("mma.sync.aligned.m16n8k8.row.col.f32.bf16.bf16.f32 {%0,%1,%2,%3}, {%4,%5}, {%6}, {%0,%1,%2,%3};"
                 : "+f"(d[0]), "+f"(d[1]), "+f"(d[2]), "+f"(d[3])
                 : "r"(a0), "r"(a1), "r"(b0));
}

__global__ void __launch_bounds__(P1_THREADS, 2)
part_kernel(const int* __restrict__ idx_in, const int* __restrict__ idx_out,
            const uint16_t* __restrict__ angle, int T, int nchunks)
{
    extern __shared__ __align__(16) uint2 stage[];
    __shared__ __align__(16) uint32_t s_off[NB_PAD];
    __shared__ __align__(16) int      s_delta[NB_PAD];
    __shared__ uint32_t s_warp[P1_THREADS / 32];

    const int tid = threadIdx.x;
    const int rep = blockIdx.x % NREP;
    uint2* const gq = g_q + (size_t)rep * CAPQ;

    int4 o[4], in[4];
    uint2 a[4];
    auto load_chunk = [&](int chunk) {
#pragma unroll
        for (int j = 0; j < 4; j++) {
            int v = chunk * (C1 / 4) + j * P1_THREADS + tid;
            if (v * 4 < T) {
                o[j]  = ld_stream4(reinterpret_cast<const int4*>(idx_out) + v);
                in[j] = ld_stream4(reinterpret_cast<const int4*>(idx_in) + v);
                a[j]  = ld_stream2(reinterpret_cast<const uint2*>(angle) + v);
            } else {
                o[j] = make_int4(-1, -1, -1, -1); in[j] = make_int4(0, 0, 0, 0); a[j] = make_uint2(0, 0);
            }
        }
    };
    load_chunk(blockIdx.x);

    for (int chunk = blockIdx.x; chunk < nchunks; chunk += gridDim.x) {
        reinterpret_cast<uint4*>(s_off)[tid] = make_uint4(0, 0, 0, 0);
        __syncthreads();
        uint32_t rx[16], ry[16];
#pragma unroll
        for (int j = 0; j < 4; j++) {
            const int ov[4] = {o[j].x, o[j].y, o[j].z, o[j].w};
            const int iv[4] = {in[j].x, in[j].y, in[j].z, in[j].w};
            const uint32_t av[4] = {a[j].x & 0xffffu, a[j].x >> 16, a[j].y & 0xffffu, a[j].y >> 16};
#pragma unroll
            for (int k = 0; k < 4; k++) {
                uint32_t bb = ((uint32_t)ov[k] >> EB_LOG) & 0xffffu;
                rx[j * 4 + k] = (uint32_t)iv[k] | ((uint32_t)(ov[k] & (EB - 1)) << IDX_BITS);
                ry[j * 4 + k] = av[k] | (bb << 16);
                if (ov[k] >= 0) atomicAdd(&s_off[bb], 1u);
            }
        }
        __syncthreads();

        const uint4 c = make_uint4(s_off[tid], s_off[tid + P1_THREADS], s_off[tid + 2 * P1_THREADS], s_off[tid + 3 * P1_THREADS]);
        const uint4 cp = make_uint4((c.x + 3u) & ~3u, (c.y + 3u) & ~3u, (c.z + 3u) & ~3u, (c.w + 3u) & ~3u);
        uint32_t* cnt = g_cnt + rep * NB_PAD + tid;
        uint32_t g0 = cp.x ? atomicAdd(cnt, cp.x) : 0u;
        uint32_t g1 = cp.y ? atomicAdd(cnt + P1_THREADS, cp.y) : 0u;
        uint32_t g2 = cp.z ? atomicAdd(cnt + 2 * P1_THREADS, cp.z) : 0u;
        uint32_t g3 = cp.w ? atomicAdd(cnt + 3 * P1_THREADS, cp.w) : 0u;
        uint32_t sum = cp.x + cp.y + cp.z + cp.w;
        uint32_t inc = sum;
#pragma unroll
        for (int d = 1; d < 32; d <<= 1) {
            uint32_t t = __shfl_up_sync(0xffffffffu, inc, d);
            if ((tid & 31) >= d) inc += t;
        }
        if ((tid & 31) == 31) s_warp[tid >> 5] = inc;
        __syncthreads();
        uint32_t wpre, total;
        {
            uint32_t x = ((tid & 31) < P1_THREADS / 32) ? s_warp[tid & 31] : 0u;
#pragma unroll
            for (int d = 1; d < P1_THREADS / 32; d <<= 1) {
                uint32_t t = __shfl_up_sync(0xffffffffu, x, d);
                if ((tid & 31) >= d) x += t;
            }
            total = __shfl_sync(0xffffffffu, x, P1_THREADS / 32 - 1);
            wpre = __shfl_sync(0xffffffffu, x, ((tid >> 5) + 31) & 31);
            if ((tid >> 5) == 0) wpre = 0;
        }
        const uint32_t ex = wpre + inc - sum;
        s_off[tid] = ex; s_off[tid + P1_THREADS] = ex + cp.x;
        s_off[tid + 2 * P1_THREADS] = ex + cp.x + cp.y; s_off[tid + 3 * P1_THREADS] = ex + cp.x + cp.y + cp.z;
        const bool spill = total > (uint32_t)STAGE_CAP;
        if (spill) {
            s_delta[tid] = (int)(g0 - ex); s_delta[tid + P1_THREADS] = (int)(g1 - (ex + cp.x));
            s_delta[tid + 2 * P1_THREADS] = (int)(g2 - (ex + cp.x + cp.y));
            s_delta[tid + 3 * P1_THREADS] = (int)(g3 - (ex + cp.x + cp.y + cp.z));
        }
        __syncthreads();

#pragma unroll
        for (int k = 0; k < 16; k++) {
            uint32_t b = ry[k] >> 16;
            if (b != 0xffffu) {
                uint32_t p = atomicAdd(&s_off[b], 1u);
                uint2 r = make_uint2(rx[k], ry[k]);
                if (p < (uint32_t)STAGE_CAP) stage[p] = r;
                else {
                    uint32_t gp = p + s_delta[b];
                    if (gp < (uint32_t)CAPQ) gq[(size_t)b * (NREP * CAPQ) + gp] = r;
                }
            }
        }
        if (!spill) {
            s_delta[tid] = (int)(g0 - ex); s_delta[tid + P1_THREADS] = (int)(g1 - (ex + cp.x));
            s_delta[tid + 2 * P1_THREADS] = (int)(g2 - (ex + cp.x + cp.y));
            s_delta[tid + 3 * P1_THREADS] = (int)(g3 - (ex + cp.x + cp.y + cp.z));
        }
        if (chunk + (int)gridDim.x < nchunks) load_chunk(chunk + gridDim.x);
        __syncthreads();
#pragma unroll
        for (int k = 0; k < 4; k++) {
            const uint32_t b = tid + k * P1_THREADS;
            for (uint32_t p = s_off[b]; p & 3u; p++) {
                uint2 d = make_uint2(0xffffffffu, b << 16);
                if (p < (uint32_t)STAGE_CAP) stage[p] = d;
                else {
                    uint32_t gp = p + s_delta[b];
                    if (gp < (uint32_t)CAPQ) gq[(size_t)b * (NREP * CAPQ) + gp] = d;
                }
            }
        }
        __syncthreads();

        const int n = min((int)total, STAGE_CAP);
#pragma unroll 4
        for (int i = tid; i < n; i += P1_THREADS) {
            uint2 r = stage[i];
            uint32_t b = r.y >> 16;
            uint32_t p = (uint32_t)(i + s_delta[b]);
            if (p < (uint32_t)CAPQ) gq[(size_t)b * (NREP * CAPQ) + p] = r;
        }
        __syncthreads();
    }
}

__global__ void __launch_bounds__(P2_THREADS, 2)
edge_kernel(const uint16_t* __restrict__ m, const int* __restrict__ idx_in, const int* __restrict__ idx_out,
            const uint16_t* __restrict__ dist, const uint16_t* __restrict__ angle,
            const uint16_t* __restrict__ centers, const uint16_t* __restrict__ ang_freq,
            const uint16_t* __restrict__ w_rbf, const uint16_t* __restrict__ w_sbf,
            const uint16_t* __restrict__ w_down, const uint16_t* __restrict__ w_up,
            uint16_t* __restrict__ out, int E, int T)
{
    extern __shared__ __align__(16) uint4 srec[];
    __shared__ uint32_t s_start[EB + 1];
    __shared__ uint32_t s_wsum[EB / 32];
    __shared__ uint32_t s_n[NREP];

    const int tid  = threadIdx.x;
    const int lane = tid & 31;
    const int warp = tid >> 5;
    const int g    = lane >> 2;
    const int t    = lane & 3;
    const int b    = blockIdx.x;

    if (tid < NREP) { s_n[tid] = g_cnt[tid * NB_PAD + b]; g_cnt[tid * NB_PAD + b] = 0; }
    if (tid < EB) s_start[tid] = 0;
    const float f0 = bf16_bits_to_f(ang_freq[0]);
    const float f1 = bf16_bits_to_f(ang_freq[1]);
    const float f2 = bf16_bits_to_f(ang_freq[2]);
    __syncthreads();
    const uint32_t n0 = s_n[0], n1 = s_n[1], n2 = s_n[2], n3 = s_n[3];
    const uint32_t e1 = n0 + n1, e2 = e1 + n2, n = e2 + n3;

    float S[2][3][4];
#pragma unroll
    for (int h = 0; h < 2; h++)
#pragma unroll
        for (int l = 0; l < 3; l++)
#pragma unroll
            for (int j = 0; j < 4; j++) S[h][l][j] = 0.f;

    bool fast = n <= (uint32_t)CAPR && max(max(n0, n1), max(n2, n3)) <= (uint32_t)CAPQ;
    uint32_t w[P2_RPT], av[P2_RPT], rk[P2_RPT];
    if (fast) {
        const uint2* gq = g_q + (size_t)b * (NREP * CAPQ);
#pragma unroll
        for (int k = 0; k < P2_RPT / 2; k++) {
            uint32_t i = 2 * (tid + k * P2_THREADS);
            uint4 v = make_uint4(0xffffffffu, 0, 0xffffffffu, 0);
            uint32_t q = i < n0 ? i : i < e1 ? i - n0 + CAPQ : i < e2 ? i - e1 + 2 * CAPQ : i - e2 + 3 * CAPQ;
            if (i < n) v = __ldcs(reinterpret_cast<const uint4*>(gq + q));
            w[2 * k] = v.x; av[2 * k] = v.y & 0xffffu; w[2 * k + 1] = v.z; av[2 * k + 1] = v.w & 0xffffu;
        }
#pragma unroll
        for (int k = 0; k < P2_RPT; k++)
            if (w[k] != 0xffffffffu) rk[k] = atomicAdd(&s_start[w[k] >> IDX_BITS], 1u);
        __syncthreads();
        uint32_t cnt = 0, inc = 0;
        if (tid < EB) {
            cnt = s_start[tid];
            inc = cnt;
#pragma unroll
            for (int d = 1; d < 32; d <<= 1) {
                uint32_t x = __shfl_up_sync(0xffffffffu, inc, d);
                if (lane >= d) inc += x;
            }
            if (lane == 31) s_wsum[warp] = inc;
        }
        __syncthreads();
        if (tid < EB) {
            uint32_t pre = 0;
#pragma unroll
            for (int x = 0; x < EB / 32; x++) pre += (x < warp) ? s_wsum[x] : 0u;
            s_start[tid] = pre + inc - cnt;
            if (tid == EB - 1) s_start[EB] = pre + inc;
        }
        __syncthreads();
        fast = s_start[EB] <= (uint32_t)CAP;
    }
    if (fast) {
#pragma unroll
        for (int k = 0; k < P2_RPT; k++) {
            if (w[k] != 0xffffffffu) {
                uint32_t p = s_start[w[k] >> IDX_BITS] + rk[k];
                float an = bf16_bits_to_f(av[k]);
                srec[p] = make_uint4((w[k] & ((1u << IDX_BITS) - 1)) * 32u,
                                     __float_as_uint(cbf_val(f0, an)),
                                     __float_as_uint(cbf_val(f1, an)),
                                     __float_as_uint(cbf_val(f2, an)));
            }
        }
        __syncthreads();

        const char* mbase = reinterpret_cast<const char*>(m) + t * 8;
#pragma unroll
        for (int h = 0; h < 2; h++) {
            const int el = 16 * warp + 8 * h + g;
            const uint32_t s = s_start[el], en = s_start[el + 1];
            for (uint32_t i = s; i < en; i += 4) {
                uint4 r[4]; uint2 v[4];
#pragma unroll
                for (int u = 0; u < 4; u++) {
                    if (i + u < en) {
                        r[u] = srec[i + u];
                        v[u] = __ldg(reinterpret_cast<const uint2*>(mbase + r[u].x));
                    } else {
                        r[u] = make_uint4(0, 0, 0, 0); v[u] = make_uint2(0, 0);
                    }
                }
#pragma unroll
                for (int u = 0; u < 4; u++) {
                    float x0 = __uint_as_float(v[u].x << 16), x1 = __uint_as_float(v[u].x & 0xffff0000u);
                    float x2 = __uint_as_float(v[u].y << 16), x3 = __uint_as_float(v[u].y & 0xffff0000u);
                    float c0 = __uint_as_float(r[u].y), c1 = __uint_as_float(r[u].z), c2 = __uint_as_float(r[u].w);
                    S[h][0][0] = fmaf(c0, x0, S[h][0][0]); S[h][0][1] = fmaf(c0, x1, S[h][0][1]);
                    S[h][0][2] = fmaf(c0, x2, S[h][0][2]); S[h][0][3] = fmaf(c0, x3, S[h][0][3]);
                    S[h][1][0] = fmaf(c1, x0, S[h][1][0]); S[h][1][1] = fmaf(c1, x1, S[h][1][1]);
                    S[h][1][2] = fmaf(c1, x2, S[h][1][2]); S[h][1][3] = fmaf(c1, x3, S[h][1][3]);
                    S[h][2][0] = fmaf(c2, x0, S[h][2][0]); S[h][2][1] = fmaf(c2, x1, S[h][2][1]);
                    S[h][2][2] = fmaf(c2, x2, S[h][2][2]); S[h][2][3] = fmaf(c2, x3, S[h][2][3]);
                }
            }
        }
    } else {
        float* sacc = reinterpret_cast<float*>(srec);
        for (int i = tid; i < EB * 48; i += P2_THREADS) sacc[i] = 0.f;
        __syncthreads();
        for (int i = tid; i < T; i += P2_THREADS) {
            int o = idx_out[i];
            if ((o >> EB_LOG) == b) {
                float an = bf16_bits_to_f(angle[i]);
                float c[3] = {cbf_val(f0, an), cbf_val(f1, an), cbf_val(f2, an)};
                const uint16_t* row = m + (size_t)idx_in[i] * 16;
                float* dst = sacc + (o & (EB - 1)) * 48;
                for (int k = 0; k < 16; k++) {
                    float x = bf16_bits_to_f(row[k]);
                    atomicAdd(dst + k, c[0] * x);
                    atomicAdd(dst + 16 + k, c[1] * x);
                    atomicAdd(dst + 32 + k, c[2] * x);
                }
            }
        }
        __syncthreads();
#pragma unroll
        for (int h = 0; h < 2; h++) {
            const int el = 16 * warp + 8 * h + g;
#pragma unroll
            for (int l = 0; l < 3; l++)
#pragma unroll
                for (int j = 0; j < 4; j++) S[h][l][j] = sacc[el * 48 + l * 16 + 4 * t + j];
        }
    }

    const int eA = b * EB + 16 * warp + g;
    const int eB = eA + 8;
    const bool okA = eA < E, okB = eB < E;

    const float cA = bf16_bits_to_f(centers[2 * t]), cB = bf16_bits_to_f(centers[2 * t + 1]);
    const float dA = okA ? bf16_bits_to_f(dist[eA]) : 0.f;
    const float dB = okB ? bf16_bits_to_f(dist[eB]) : 0.f;
    const uint32_t ra0 = pack_bf16(rbf_val(dA, cA), rbf_val(dA, cB));
    const uint32_t ra1 = pack_bf16(rbf_val(dB, cA), rbf_val(dB, cB));

    auto ld2 = [](const uint16_t* p0, const uint16_t* p1) -> uint32_t {
        return (uint32_t)__ldg(p0) | ((uint32_t)__ldg(p1) << 16);
    };

    float y[3][2][4];
#pragma unroll
    for (int tl = 0; tl < 3; tl++)
#pragma unroll
        for (int j = 0; j < 2; j++)
#pragma unroll
            for (int i = 0; i < 4; i++) y[tl][j][i] = 0.f;
    {
        uint32_t wd[2][2];
#pragma unroll
        for (int j = 0; j < 2; j++) {
            wd[j][0] = ld2(w_down + (4 * t + 0) * 16 + 8 * j + g, w_down + (4 * t + 1) * 16 + 8 * j + g);
            wd[j][1] = ld2(w_down + (4 * t + 2) * 16 + 8 * j + g, w_down + (4 * t + 3) * 16 + 8 * j + g);
        }
#pragma unroll
        for (int tl = 0; tl < 3; tl++) {
            const float* P = (tl == 0) ? S[0][0] : (tl == 1) ? S[1][0] : S[0][2];
            const float* Q = (tl == 0) ? S[0][1] : (tl == 1) ? S[1][1] : S[1][2];
            uint32_t h0 = pack_bf16(P[0], P[1]), h1 = pack_bf16(Q[0], Q[1]);
            uint32_t h2 = pack_bf16(P[2], P[3]), h3 = pack_bf16(Q[2], Q[3]);
            uint32_t l0 = pack_bf16(P[0] - __uint_as_float(h0 << 16), P[1] - __uint_as_float(h0 & 0xffff0000u));
            uint32_t l1 = pack_bf16(Q[0] - __uint_as_float(h1 << 16), Q[1] - __uint_as_float(h1 & 0xffff0000u));
            uint32_t l2 = pack_bf16(P[2] - __uint_as_float(h2 << 16), P[3] - __uint_as_float(h2 & 0xffff0000u));
            uint32_t l3 = pack_bf16(Q[2] - __uint_as_float(h3 << 16), Q[3] - __uint_as_float(h3 & 0xffff0000u));
#pragma unroll
            for (int j = 0; j < 2; j++) {
                mma16816(y[tl][j], h0, h1, h2, h3, wd[j][0], wd[j][1]);
                mma16816(y[tl][j], l0, l1, l2, l3, wd[j][0], wd[j][1]);
            }
        }
    }
    float aggA[2][2] = {{0.f, 0.f}, {0.f, 0.f}}, aggB[2][2] = {{0.f, 0.f}, {0.f, 0.f}};
#pragma unroll
    for (int l = 0; l < 3; l++) {
#pragma unroll
        for (int j = 0; j < 2; j++) {
            uint32_t ws = ld2(w_sbf + (3 * (2 * t) + l) * 16 + 8 * j + g, w_sbf + (3 * (2 * t + 1) + l) * 16 + 8 * j + g);
            float G[4] = {0.f, 0.f, 0.f, 0.f};
            mma1688(G, ra0, ra1, ws);
            float ya0, ya1, yb0, yb1;
            if (l == 0)      { ya0 = y[0][j][0]; ya1 = y[0][j][1]; yb0 = y[1][j][0]; yb1 = y[1][j][1]; }
            else if (l == 1) { ya0 = y[0][j][2]; ya1 = y[0][j][3]; yb0 = y[1][j][2]; yb1 = y[1][j][3]; }
            else             { ya0 = y[2][j][0]; ya1 = y[2][j][1]; yb0 = y[2][j][2]; yb1 = y[2][j][3]; }
            aggA[j][0] = fmaf(ya0, G[0], aggA[j][0]); aggA[j][1] = fmaf(ya1, G[1], aggA[j][1]);
            aggB[j][0] = fmaf(yb0, G[2], aggB[j][0]); aggB[j][1] = fmaf(yb1, G[3], aggB[j][1]);
        }
    }
    float u[2][4], rw[2][4];
    {
        uint32_t h0 = pack_bf16(aggA[0][0], aggA[0][1]), h1 = pack_bf16(aggB[0][0], aggB[0][1]);
        uint32_t h2 = pack_bf16(aggA[1][0], aggA[1][1]), h3 = pack_bf16(aggB[1][0], aggB[1][1]);
        uint32_t l0 = pack_bf16(aggA[0][0] - __uint_as_float(h0 << 16), aggA[0][1] - __uint_as_float(h0 & 0xffff0000u));
        uint32_t l1 = pack_bf16(aggB[0][0] - __uint_as_float(h1 << 16), aggB[0][1] - __uint_as_float(h1 & 0xffff0000u));
        uint32_t l2 = pack_bf16(aggA[1][0] - __uint_as_float(h2 << 16), aggA[1][1] - __uint_as_float(h2 & 0xffff0000u));
        uint32_t l3 = pack_bf16(aggB[1][0] - __uint_as_float(h3 << 16), aggB[1][1] - __uint_as_float(h3 & 0xffff0000u));
#pragma unroll
        for (int j = 0; j < 2; j++) {
            const int col = 4 * (g >> 1) + 2 * j + (g & 1);
            uint32_t b0 = ld2(w_up + (2 * t) * 16 + col, w_up + (2 * t + 1) * 16 + col);
            uint32_t b1 = ld2(w_up + (2 * t + 8) * 16 + col, w_up + (2 * t + 9) * 16 + col);
            uint32_t br = ld2(w_rbf + (2 * t) * 16 + col, w_rbf + (2 * t + 1) * 16 + col);
#pragma unroll
            for (int i = 0; i < 4; i++) { u[j][i] = 0.f; rw[j][i] = 0.f; }
            mma16816(u[j], h0, h1, h2, h3, b0, b1);
            mma16816(u[j], l0, l1, l2, l3, b0, b1);
            mma1688(rw[j], ra0, ra1, br);
        }
    }
    if (okA) {
        uint2 mv = __ldg(reinterpret_cast<const uint2*>(m + (size_t)eA * 16 + 4 * t));
        float o0 = fmaf(u[0][0], rw[0][0], __uint_as_float(mv.x << 16));
        float o1 = fmaf(u[0][1], rw[0][1], __uint_as_float(mv.x & 0xffff0000u));
        float o2 = fmaf(u[1][0], rw[1][0], __uint_as_float(mv.y << 16));
        float o3 = fmaf(u[1][1], rw[1][1], __uint_as_float(mv.y & 0xffff0000u));
        *reinterpret_cast<uint2*>(out + (size_t)eA * 16 + 4 * t) = make_uint2(pack_bf16(o0, o1), pack_bf16(o2, o3));
    }
    if (okB) {
        uint2 mv = __ldg(reinterpret_cast<const uint2*>(m + (size_t)eB * 16 + 4 * t));
        float o0 = fmaf(u[0][2], rw[0][2], __uint_as_float(mv.x << 16));
        float o1 = fmaf(u[0][3], rw[0][3], __uint_as_float(mv.x & 0xffff0000u));
        float o2 = fmaf(u[1][2], rw[1][2], __uint_as_float(mv.y << 16));
        float o3 = fmaf(u[1][3], rw[1][3], __uint_as_float(mv.y & 0xffff0000u));
        *reinterpret_cast<uint2*>(out + (size_t)eB * 16 + 4 * t) = make_uint2(pack_bf16(o0, o1), pack_bf16(o2, o3));
    }
}

}

extern "C" void kernel_launch(void* const* d_in, const int* in_sizes, int n_in,
                              void* d_out, int out_size) {
    const uint16_t* m        = (const uint16_t*)d_in[0];
    const int*      idx_in   = (const int*)d_in[1];
    const int*      idx_out  = (const int*)d_in[2];
    const uint16_t* dist     = (const uint16_t*)d_in[3];
    const uint16_t* angle    = (const uint16_t*)d_in[4];
    const uint16_t* centers  = (const uint16_t*)d_in[5];
    const uint16_t* ang_freq = (const uint16_t*)d_in[6];
    const uint16_t* w_rbf    = (const uint16_t*)d_in[7];
    const uint16_t* w_sbf    = (const uint16_t*)d_in[8];
    const uint16_t* w_down   = (const uint16_t*)d_in[9];
    const uint16_t* w_up     = (const uint16_t*)d_in[10];
    uint16_t* out = (uint16_t*)d_out;
    const int E = in_sizes[3];
    const int T = in_sizes[1];

    static bool init = false;
    if (!init) {
        cudaFuncSetAttribute(part_kernel, cudaFuncAttributeMaxDynamicSharedMemorySize, STAGE_CAP * 8);
        cudaFuncSetAttribute(edge_kernel, cudaFuncAttributeMaxDynamicSharedMemorySize, CAP * 16);
        init = true;
    }
    const int nb = (E + EB - 1) / EB;
    const int nchunks = (T + C1 - 1) / C1;
    part_kernel<<<min(nchunks, 264), P1_THREADS, STAGE_CAP * 8>>>(idx_in, idx_out, angle, T, nchunks);
    edge_kernel<<<nb, P2_THREADS, CAP * 16>>>(m, idx_in, idx_out, dist, angle, centers, ang_freq,
                                              w_rbf, w_sbf, w_down, w_up, out, E, T);
}
```

```cpp
#include <cuda_runtime.h>
#include <cuda_bf16.h>
#include <stdint.h>

namespace {

constexpr int kMaxE   = 400000;
constexpr int IDX_BITS = 19;
constexpr int EB_LOG  = 8;
constexpr int EB      = 1 << EB_LOG;
constexpr int NB_MAX  = (kMaxE + EB - 1) / EB;
constexpr int NB_PAD  = 2048;
constexpr int CAP     = 4608;
constexpr int CAPR    = 6144;
constexpr int NREP    = 4;
constexpr int CAPQ    = 1664;
constexpr int STAGE_CAP = 11264;

constexpr int P1_THREADS = 1024;
constexpr int P1_RPT     = 8;
constexpr int P1_V       = P1_RPT / 4;
constexpr int P1_BPT     = NB_PAD / P1_THREADS;
constexpr int C1         = P1_THREADS * P1_RPT;

constexpr int P2_THREADS = 512;
constexpr int P2_RPT     = CAPR / P2_THREADS;

__device__ uint32_t g_cnt[NREP * NB_PAD];
__device__ __align__(128) uint2 g_q[(size_t)NB_MAX * NREP * CAPQ];

__device__ __forceinline__ int4 ld_stream4(const int4* p) { return __ldcs(p); }
__device__ __forceinline__ uint2 ld_stream2(const uint2* p) { return __ldcs(p); }

__device__ __forceinline__ float bf16r(float x) { return __bfloat162float(__float2bfloat16_rn(x)); }
__device__ __forceinline__ float bf16_bits_to_f(uint32_t h) { return __uint_as_float(h << 16); }
__device__ __forceinline__ uint32_t pack_bf16(float lo, float hi) {
    __nv_bfloat162 v = __floats2bfloat162_rn(lo, hi);
    return *reinterpret_cast<uint32_t*>(&v);
}

__device__ __noinline__ float cos_slow(float x) { return cosf(x); }
__device__ __forceinline__ float cos_acc(float x) {
    if (fabsf(x) > 1000.f) return cos_slow(x);
    float k = rintf(x * 0.15915494309189535f);
    float r = fmaf(k, -6.28318548202514648f, x);
    r = fmaf(k, 1.7484555314695172e-7f, r);
    return __cosf(r);
}
__device__ __forceinline__ float cbf_val(float freq, float ang) {
    return bf16r(cos_acc(bf16r(freq * ang)));
}
__device__ __forceinline__ float rbf_val(float d, float c) {
    float x = bf16r(d - c);
    float s = bf16r(x * x);
    float a = bf16r(-10.f * s);
    return bf16r(expf(a));
}

__device__ __forceinline__ void mma16816(float* d, uint32_t a0, uint32_t a1, uint32_t a2, uint32_t a3,
                                         uint32_t b0, uint32_t b1) {
    asm volatile("mma.sync.aligned.m16n8k16.row.col.f32.bf16.bf16.f32 {%0,%1,%2,%3}, {%4,%5,%6,%7}, {%8,%9}, {%0,%1,%2,%3};"
                 : "+f"(d[0]), "+f"(d[1]), "+f"(d[2]), "+f"(d[3])
                 : "r"(a0), "r"(a1), "r"(a2), "r"(a3), "r"(b0), "r"(b1));
}
__device__ __forceinline__ void mma1688(float* d, uint32_t a0, uint32_t a1, uint32_t b0) {
    asm volatile("mma.sync.aligned.m16n8k8.row.col.f32.bf16.bf16.f32 {%0,%1,%2,%3}, {%4,%5}, {%6}, {%0,%1,%2,%3};"
                 : "+f"(d[0]), "+f"(d[1]), "+f"(d[2]), "+f"(d[3])
                 : "r"(a0), "r"(a1), "r"(b0));
}

__global__ void __launch_bounds__(P1_THREADS, 2)
part_kernel(const int* __restrict__ idx_in, const int* __restrict__ idx_out,
            const uint16_t* __restrict__ angle, int T, int nchunks)
{
    extern __shared__ __align__(16) uint2 stage[];
    __shared__ __align__(16) uint32_t s_off[NB_PAD];
    __shared__ __align__(16) int      s_delta[NB_PAD];
    __shared__ uint32_t s_warp[32];

    const int tid = threadIdx.x;
    const int rep = blockIdx.x % NREP;
    uint2* const gq = g_q + (size_t)rep * CAPQ;

    int4 o[P1_V], in[P1_V];
    uint2 a[P1_V];
    auto load_chunk = [&](int chunk) {
#pragma unroll
        for (int j = 0; j < P1_V; j++) {
            int v = chunk * (C1 / 4) + j * P1_THREADS + tid;
            if (v * 4 < T) {
                o[j]  = ld_stream4(reinterpret_cast<const int4*>(idx_out) + v);
                in[j] = ld_stream4(reinterpret_cast<const int4*>(idx_in) + v);
                a[j]  = ld_stream2(reinterpret_cast<const uint2*>(angle) + v);
            } else {
                o[j] = make_int4(-1, -1, -1, -1); in[j] = make_int4(0, 0, 0, 0); a[j] = make_uint2(0, 0);
            }
        }
    };
    load_chunk(blockIdx.x);

    for (int chunk = blockIdx.x; chunk < nchunks; chunk += gridDim.x) {
#pragma unroll
        for (int k = 0; k < P1_BPT; k++) s_off[tid + k * P1_THREADS] = 0;
        __syncthreads();
        uint32_t rx[P1_RPT], ry[P1_RPT];
#pragma unroll
        for (int j = 0; j < P1_V; j++) {
            const int ov[4] = {o[j].x, o[j].y, o[j].z, o[j].w};
            const int iv[4] = {in[j].x, in[j].y, in[j].z, in[j].w};
            const uint32_t av[4] = {a[j].x & 0xffffu, a[j].x >> 16, a[j].y & 0xffffu, a[j].y >> 16};
#pragma unroll
            for (int k = 0; k < 4; k++) {
                uint32_t bb = ((uint32_t)ov[k] >> EB_LOG) & 0xffffu;
                rx[j * 4 + k] = (uint32_t)iv[k] | ((uint32_t)(ov[k] & (EB - 1)) << IDX_BITS);
                ry[j * 4 + k] = av[k] | (bb << 16);
                if (ov[k] >= 0) atomicAdd(&s_off[bb], 1u);
            }
        }
        __syncthreads();

        uint32_t cp[P1_BPT], g[P1_BPT];
        uint32_t sum = 0;
#pragma unroll
        for (int k = 0; k < P1_BPT; k++) {
            cp[k] = (s_off[tid + k * P1_THREADS] + 3u) & ~3u;
            g[k] = cp[k] ? atomicAdd(g_cnt + rep * NB_PAD + tid + k * P1_THREADS, cp[k]) : 0u;
            sum += cp[k];
        }
        uint32_t inc = sum;
#pragma unroll
        for (int d = 1; d < 32; d <<= 1) {
            uint32_t t = __shfl_up_sync(0xffffffffu, inc, d);
            if ((tid & 31) >= d) inc += t;
        }
        if ((tid & 31) == 31) s_warp[tid >> 5] = inc;
        __syncthreads();
        uint32_t wpre, total;
        {
            uint32_t x = ((tid & 31) < P1_THREADS / 32) ? s_warp[tid & 31] : 0u;
#pragma unroll
            for (int d = 1; d < P1_THREADS / 32; d <<= 1) {
                uint32_t t = __shfl_up_sync(0xffffffffu, x, d);
                if ((tid & 31) >= d) x += t;
            }
            total = __shfl_sync(0xffffffffu, x, P1_THREADS / 32 - 1);
            wpre = __shfl_sync(0xffffffffu, x, ((tid >> 5) + 31) & 31);
            if ((tid >> 5) == 0) wpre = 0;
        }
        const uint32_t ex = wpre + inc - sum;
        const bool spill = total > (uint32_t)STAGE_CAP;
        {
            uint32_t e = ex;
#pragma unroll
            for (int k = 0; k < P1_BPT; k++) {
                s_off[tid + k * P1_THREADS] = e;
                if (spill) s_delta[tid + k * P1_THREADS] = (int)(g[k] - e);
                e += cp[k];
            }
        }
        __syncthreads();

#pragma unroll
        for (int k = 0; k < P1_RPT; k++) {
            uint32_t b = ry[k] >> 16;
            if (b != 0xffffu) {
                uint32_t p = atomicAdd(&s_off[b], 1u);
                uint2 r = make_uint2(rx[k], ry[k]);
                if (p < (uint32_t)STAGE_CAP) stage[p] = r;
                else {
                    uint32_t gp = p + s_delta[b];
                    if (gp < (uint32_t)CAPQ) gq[(size_t)b * (NREP * CAPQ) + gp] = r;
                }
            }
        }
        if (!spill) {
            uint32_t e = ex;
#pragma unroll
            for (int k = 0; k < P1_BPT; k++) {
                s_delta[tid + k * P1_THREADS] = (int)(g[k] - e);
                e += cp[k];
            }
        }
        if (chunk + (int)gridDim.x < nchunks) load_chunk(chunk + gridDim.x);
        __syncthreads();
#pragma unroll
        for (int k = 0; k < P1_BPT; k++) {
            const uint32_t b = tid + k * P1_THREADS;
            for (uint32_t p = s_off[b]; p & 3u; p++) {
                uint2 d = make_uint2(0xffffffffu, b << 16);
                if (p < (uint32_t)STAGE_CAP) stage[p] = d;
                else {
                    uint32_t gp = p + s_delta[b];
                    if (gp < (uint32_t)CAPQ) gq[(size_t)b * (NREP * CAPQ) + gp] = d;
                }
            }
        }
        __syncthreads();

        const int n = min((int)total, STAGE_CAP);
#pragma unroll 2
        for (int i = tid; i < n; i += P1_THREADS) {
            uint2 r = stage[i];
            uint32_t b = r.y >> 16;
            uint32_t p = (uint32_t)(i + s_delta[b]);
            if (p < (uint32_t)CAPQ) gq[(size_t)b * (NREP * CAPQ) + p] = r;
        }
        __syncthreads();
    }
}

__global__ void __launch_bounds__(P2_THREADS, 2)
edge_kernel(const uint16_t* __restrict__ m, const int* __restrict__ idx_in, const int* __restrict__ idx_out,
            const uint16_t* __restrict__ dist, const uint16_t* __restrict__ angle,
            const uint16_t* __restrict__ centers, const uint16_t* __restrict__ ang_freq,
            const uint16_t* __restrict__ w_rbf, const uint16_t* __restrict__ w_sbf,
            const uint16_t* __restrict__ w_down, const uint16_t* __restrict__ w_up,
            uint16_t* __restrict__ out, int E, int T)
{
    extern __shared__ __align__(16) uint4 srec[];
    __shared__ uint32_t s_start[EB + 1];
    __shared__ uint32_t s_wsum[EB / 32];
    __shared__ uint32_t s_n[NREP];

    const int tid  = threadIdx.x;
    const int lane = tid & 31;
    const int warp = tid >> 5;
    const int g    = lane >> 2;
    const int t    = lane & 3;
    const int b    = blockIdx.x;

    if (tid < NREP) { s_n[tid] = g_cnt[tid * NB_PAD + b]; g_cnt[tid * NB_PAD + b] = 0; }
    if (tid < EB) s_start[tid] = 0;
    const float f0 = bf16_bits_to_f(ang_freq[0]);
    const float f1 = bf16_bits_to_f(ang_freq[1]);
    const float f2 = bf16_bits_to_f(ang_freq[2]);
    __syncthreads();
    const uint32_t n0 = s_n[0], n1 = s_n[1], n2 = s_n[2], n3 = s_n[3];
    const uint32_t e1 = n0 + n1, e2 = e1 + n2, n = e2 + n3;

    float S[2][3][4];
#pragma unroll
    for (int h = 0; h < 2; h++)
#pragma unroll
        for (int l = 0; l < 3; l++)
#pragma unroll
            for (int j = 0; j < 4; j++) S[h][l][j] = 0.f;

    bool fast = n <= (uint32_t)CAPR && max(max(n0, n1), max(n2, n3)) <= (uint32_t)CAPQ;
    uint32_t w[P2_RPT], av[P2_RPT], rk[P2_RPT];
    if (fast) {
        const uint2* gq = g_q + (size_t)b * (NREP * CAPQ);
#pragma unroll
        for (int k = 0; k < P2_RPT / 2; k++) {
            uint32_t i = 2 * (tid + k * P2_THREADS);
            uint4 v = make_uint4(0xffffffffu, 0, 0xffffffffu, 0);
            uint32_t q = i < n0 ? i : i < e1 ? i - n0 + CAPQ : i < e2 ? i - e1 + 2 * CAPQ : i - e2 + 3 * CAPQ;
            if (i < n) v = __ldcs(reinterpret_cast<const uint4*>(gq + q));
            w[2 * k] = v.x; av[2 * k] = v.y & 0xffffu; w[2 * k + 1] = v.z; av[2 * k + 1] = v.w & 0xffffu;
        }
#pragma unroll
        for (int k = 0; k < P2_RPT; k++)
            if (w[k] != 0xffffffffu) rk[k] = atomicAdd(&s_start[w[k] >> IDX_BITS], 1u);
        __syncthreads();
        uint32_t cnt = 0, inc = 0;
        if (tid < EB) {
            cnt = s_start[tid];
            inc = cnt;
#pragma unroll
            for (int d = 1; d < 32; d <<= 1) {
                uint32_t x = __shfl_up_sync(0xffffffffu, inc, d);
                if (lane >= d) inc += x;
            }
            if (lane == 31) s_wsum[warp] = inc;
        }
        __syncthreads();
        if (tid < EB) {
            uint32_t pre = 0;
#pragma unroll
            for (int x = 0; x < EB / 32; x++) pre += (x < warp) ? s_wsum[x] : 0u;
            s_start[tid] = pre + inc - cnt;
            if (tid == EB - 1) s_start[EB] = pre + inc;
        }
        __syncthreads();
        fast = s_start[EB] <= (uint32_t)CAP;
    }
    if (fast) {
#pragma unroll
        for (int k = 0; k < P2_RPT; k++) {
            if (w[k] != 0xffffffffu) {
                uint32_t p = s_start[w[k] >> IDX_BITS] + rk[k];
                float an = bf16_bits_to_f(av[k]);
                srec[p] = make_uint4((w[k] & ((1u << IDX_BITS) - 1)) * 32u,
                                     __float_as_uint(cbf_val(f0, an)),
                                     __float_as_uint(cbf_val(f1, an)),
                                     __float_as_uint(cbf_val(f2, an)));
            }
        }
        __syncthreads();

        const char* mbase = reinterpret_cast<const char*>(m) + t * 8;
#pragma unroll
        for (int h = 0; h < 2; h++) {
            const int el = 16 * warp + 8 * h + g;
            const uint32_t s = s_start[el], en = s_start[el + 1];
            for (uint32_t i = s; i < en; i += 4) {
                uint4 r[4]; uint2 v[4];
#pragma unroll
                for (int u = 0; u < 4; u++) {
                    if (i + u < en) {
                        r[u] = srec[i + u];
                        v[u] = __ldg(reinterpret_cast<const uint2*>(mbase + r[u].x));
                    } else {
                        r[u] = make_uint4(0, 0, 0, 0); v[u] = make_uint2(0, 0);
                    }
                }
#pragma unroll
                for (int u = 0; u < 4; u++) {
                    float x0 = __uint_as_float(v[u].x << 16), x1 = __uint_as_float(v[u].x & 0xffff0000u);
                    float x2 = __uint_as_float(v[u].y << 16), x3 = __uint_as_float(v[u].y & 0xffff0000u);
                    float c0 = __uint_as_float(r[u].y), c1 = __uint_as_float(r[u].z), c2 = __uint_as_float(r[u].w);
                    S[h][0][0] = fmaf(c0, x0, S[h][0][0]); S[h][0][1] = fmaf(c0, x1, S[h][0][1]);
                    S[h][0][2] = fmaf(c0, x2, S[h][0][2]); S[h][0][3] = fmaf(c0, x3, S[h][0][3]);
                    S[h][1][0] = fmaf(c1, x0, S[h][1][0]); S[h][1][1] = fmaf(c1, x1, S[h][1][1]);
                    S[h][1][2] = fmaf(c1, x2, S[h][1][2]); S[h][1][3] = fmaf(c1, x3, S[h][1][3]);
                    S[h][2][0] = fmaf(c2, x0, S[h][2][0]); S[h][2][1] = fmaf(c2, x1, S[h][2][1]);
                    S[h][2][2] = fmaf(c2, x2, S[h][2][2]); S[h][2][3] = fmaf(c2, x3, S[h][2][3]);
                }
            }
        }
    } else {
        float* sacc = reinterpret_cast<float*>(srec);
        for (int i = tid; i < EB * 48; i += P2_THREADS) sacc[i] = 0.f;
        __syncthreads();
        for (int i = tid; i < T; i += P2_THREADS) {
            int o = idx_out[i];
            if ((o >> EB_LOG) == b) {
                float an = bf16_bits_to_f(angle[i]);
                float c[3] = {cbf_val(f0, an), cbf_val(f1, an), cbf_val(f2, an)};
                const uint16_t* row = m + (size_t)idx_in[i] * 16;
                float* dst = sacc + (o & (EB - 1)) * 48;
                for (int k = 0; k < 16; k++) {
                    float x = bf16_bits_to_f(row[k]);
                    atomicAdd(dst + k, c[0] * x);
                    atomicAdd(dst + 16 + k, c[1] * x);
                    atomicAdd(dst + 32 + k, c[2] * x);
                }
            }
        }
        __syncthreads();
#pragma unroll
        for (int h = 0; h < 2; h++) {
            const int el = 16 * warp + 8 * h + g;
#pragma unroll
            for (int l = 0; l < 3; l++)
#pragma unroll
                for (int j = 0; j < 4; j++) S[h][l][j] = sacc[el * 48 + l * 16 + 4 * t + j];
        }
    }

    const int eA = b * EB + 16 * warp + g;
    const int eB = eA + 8;
    const bool okA = eA < E, okB = eB < E;

    const float cA = bf16_bits_to_f(centers[2 * t]), cB = bf16_bits_to_f(centers[2 * t + 1]);
    const float dA = okA ? bf16_bits_to_f(dist[eA]) : 0.f;
    const float dB = okB ? bf16_bits_to_f(dist[eB]) : 0.f;
    const uint32_t ra0 = pack_bf16(rbf_val(dA, cA), rbf_val(dA, cB));
    const uint32_t ra1 = pack_bf16(rbf_val(dB, cA), rbf_val(dB, cB));

    auto ld2 = [](const uint16_t* p0, const uint16_t* p1) -> uint32_t {
        return (uint32_t)__ldg(p0) | ((uint32_t)__ldg(p1) << 16);
    };

    float y[3][2][4];
#pragma unroll
    for (int tl = 0; tl < 3; tl++)
#pragma unroll
        for (int j = 0; j < 2; j++)
#pragma unroll
            for (int i = 0; i < 4; i++) y[tl][j][i] = 0.f;
    {
        uint32_t wd[2][2];
#pragma unroll
        for (int j = 0; j < 2; j++) {
            wd[j][0] = ld2(w_down + (4 * t + 0) * 16 + 8 * j + g, w_down + (4 * t + 1) * 16 + 8 * j + g);
            wd[j][1] = ld2(w_down + (4 * t + 2) * 16 + 8 * j + g, w_down + (4 * t + 3) * 16 + 8 * j + g);
        }
#pragma unroll
        for (int tl = 0; tl < 3; tl++) {
            const float* P = (tl == 0) ? S[0][0] : (tl == 1) ? S[1][0] : S[0][2];
            const float* Q = (tl == 0) ? S[0][1] : (tl == 1) ? S[1][1] : S[1][2];
            uint32_t h0 = pack_bf16(P[0], P[1]), h1 = pack_bf16(Q[0], Q[1]);
            uint32_t h2 = pack_bf16(P[2], P[3]), h3 = pack_bf16(Q[2], Q[3]);
            uint32_t l0 = pack_bf16(P[0] - __uint_as_float(h0 << 16), P[1] - __uint_as_float(h0 & 0xffff0000u));
            uint32_t l1 = pack_bf16(Q[0] - __uint_as_float(h1 << 16), Q[1] - __uint_as_float(h1 & 0xffff0000u));
            uint32_t l2 = pack_bf16(P[2] - __uint_as_float(h2 << 16), P[3] - __uint_as_float(h2 & 0xffff0000u));
            uint32_t l3 = pack_bf16(Q[2] - __uint_as_float(h3 << 16), Q[3] - __uint_as_float(h3 & 0xffff0000u));
#pragma unroll
            for (int j = 0; j < 2; j++) {
                mma16816(y[tl][j], h0, h1, h2, h3, wd[j][0], wd[j][1]);
                mma16816(y[tl][j], l0, l1, l2, l3, wd[j][0], wd[j][1]);
            }
        }
    }
    float aggA[2][2] = {{0.f, 0.f}, {0.f, 0.f}}, aggB[2][2] = {{0.f, 0.f}, {0.f, 0.f}};
#pragma unroll
    for (int l = 0; l < 3; l++) {
#pragma unroll
        for (int j = 0; j < 2; j++) {
            uint32_t ws = ld2(w_sbf + (3 * (2 * t) + l) * 16 + 8 * j + g, w_sbf + (3 * (2 * t + 1) + l) * 16 + 8 * j + g);
            float G[4] = {0.f, 0.f, 0.f, 0.f};
            mma1688(G, ra0, ra1, ws);
            float ya0, ya1, yb0, yb1;
            if (l == 0)      { ya0 = y[0][j][0]; ya1 = y[0][j][1]; yb0 = y[1][j][0]; yb1 = y[1][j][1]; }
            else if (l == 1) { ya0 = y[0][j][2]; ya1 = y[0][j][3]; yb0 = y[1][j][2]; yb1 = y[1][j][3]; }
            else             { ya0 = y[2][j][0]; ya1 = y[2][j][1]; yb0 = y[2][j][2]; yb1 = y[2][j][3]; }
            aggA[j][0] = fmaf(ya0, G[0], aggA[j][0]); aggA[j][1] = fmaf(ya1, G[1], aggA[j][1]);
            aggB[j][0] = fmaf(yb0, G[2], aggB[j][0]); aggB[j][1] = fmaf(yb1, G[3], aggB[j][1]);
        }
    }
    float u[2][4], rw[2][4];
    {
        uint32_t h0 = pack_bf16(aggA[0][0], aggA[0][1]), h1 = pack_bf16(aggB[0][0], aggB[0][1]);
        uint32_t h2 = pack_bf16(aggA[1][0], aggA[1][1]), h3 = pack_bf16(aggB[1][0], aggB[1][1]);
        uint32_t l0 = pack_bf16(aggA[0][0] - __uint_as_float(h0 << 16), aggA[0][1] - __uint_as_float(h0 & 0xffff0000u));
        uint32_t l1 = pack_bf16(aggB[0][0] - __uint_as_float(h1 << 16), aggB[0][1] - __uint_as_float(h1 & 0xffff0000u));
        uint32_t l2 = pack_bf16(aggA[1][0] - __uint_as_float(h2 << 16), aggA[1][1] - __uint_as_float(h2 & 0xffff0000u));
        uint32_t l3 = pack_bf16(aggB[1][0] - __uint_as_float(h3 << 16), aggB[1][1] - __uint_as_float(h3 & 0xffff0000u));
#pragma unroll
        for (int j = 0; j < 2; j++) {
            const int col = 4 * (g >> 1) + 2 * j + (g & 1);
            uint32_t b0 = ld2(w_up + (2 * t) * 16 + col, w_up + (2 * t + 1) * 16 + col);
            uint32_t b1 = ld2(w_up + (2 * t + 8) * 16 + col, w_up + (2 * t + 9) * 16 + col);
            uint32_t br = ld2(w_rbf + (2 * t) * 16 + col, w_rbf + (2 * t + 1) * 16 + col);
#pragma unroll
            for (int i = 0; i < 4; i++) { u[j][i] = 0.f; rw[j][i] = 0.f; }
            mma16816(u[j], h0, h1, h2, h3, b0, b1);
            mma16816(u[j], l0, l1, l2, l3, b0, b1);
            mma1688(rw[j], ra0, ra1, br);
        }
    }
    if (okA) {
        uint2 mv = __ldg(reinterpret_cast<const uint2*>(m + (size_t)eA * 16 + 4 * t));
        float o0 = fmaf(u[0][0], rw[0][0], __uint_as_float(mv.x << 16));
        float o1 = fmaf(u[0][1], rw[0][1], __uint_as_float(mv.x & 0xffff0000u));
        float o2 = fmaf(u[1][0], rw[1][0], __uint_as_float(mv.y << 16));
        float o3 = fmaf(u[1][1], rw[1][1], __uint_as_float(mv.y & 0xffff0000u));
        *reinterpret_cast<uint2*>(out + (size_t)eA * 16 + 4 * t) = make_uint2(pack_bf16(o0, o1), pack_bf16(o2, o3));
    }
    if (okB) {
        uint2 mv = __ldg(reinterpret_cast<const uint2*>(m + (size_t)eB * 16 + 4 * t));
        float o0 = fmaf(u[0][2], rw[0][2], __uint_as_float(mv.x << 16));
        float o1 = fmaf(u[0][3], rw[0][3], __uint_as_float(mv.x & 0xffff0000u));
        float o2 = fmaf(u[1][2], rw[1][2], __uint_as_float(mv.y << 16));
        float o3 = fmaf(u[1][3], rw[1][3], __uint_as_float(mv.y & 0xffff0000u));
        *reinterpret_cast<uint2*>(out + (size_t)eB * 16 + 4 * t) = make_uint2(pack_bf16(o0, o1), pack_bf16(o2, o3));
    }
}

}

extern "C" void kernel_launch(void* const* d_in, const int* in_sizes, int n_in,
                              void* d_out, int out_size) {
    const uint16_t* m        = (const uint16_t*)d_in[0];
    const int*      idx_in   = (const int*)d_in[1];
    const int*      idx_out  = (const int*)d_in[2];
    const uint16_t* dist     = (const uint16_t*)d_in[3];
    const uint16_t* angle    = (const uint16_t*)d_in[4];
    const uint16_t* centers  = (const uint16_t*)d_in[5];
    const uint16_t* ang_freq = (const uint16_t*)d_in[6];
    const uint16_t* w_rbf    = (const uint16_t*)d_in[7];
    const uint16_t* w_sbf    = (const uint16_t*)d_in[8];
    const uint16_t* w_down   = (const uint16_t*)d_in[9];
    const uint16_t* w_up     = (const uint16_t*)d_in[10];
    uint16_t* out = (uint16_t*)d_out;
    const int E = in_sizes[3];
    const int T = in_sizes[1];

    static bool init = false;
    if (!init) {
        cudaFuncSetAttribute(part_kernel, cudaFuncAttributeMaxDynamicSharedMemorySize, STAGE_CAP * 8);
        cudaFuncSetAttribute(edge_kernel, cudaFuncAttributeMaxDynamicSharedMemorySize, CAP * 16);
        init = true;
    }
    const int nb = (E + EB - 1) / EB;
    const int nchunks = (T + C1 - 1) / C1;
    part_kernel<<<min(nchunks, 264), P1_THREADS, STAGE_CAP * 8>>>(idx_in, idx_out, angle, T, nchunks);
    edge_kernel<<<nb, P2_THREADS, CAP * 16>>>(m, idx_in, idx_out, dist, angle, centers, ang_freq,
                                              w_rbf, w_sbf, w_down, w_up, out, E, T);
}
```

```cpp
#include <cuda_runtime.h>
#include <cuda_bf16.h>
#include <stdint.h>

namespace {

constexpr int kMaxE   = 400000;
constexpr int kMaxT   = 6400000;
constexpr int IDX_BITS = 19;
constexpr int EB_LOG  = 8;
constexpr int EB      = 1 << EB_LOG;
constexpr int NB_MAX  = (kMaxE + EB - 1) / EB;
constexpr int NB_PAD  = 2048;
constexpr int OFF_STRIDE = 1584;
static_assert(NB_MAX + 1 <= OFF_STRIDE && NB_MAX <= NB_PAD && kMaxE <= (1 << IDX_BITS), "sizes");
constexpr int CAP     = 4480;
constexpr int CAPP    = CAP + EB + 64;

constexpr int P1_THREADS = 1024;
constexpr int P1_RPT     = 16;
constexpr int C1         = P1_THREADS * P1_RPT;
constexpr int CSTR       = (C1 + 19) / 20 * 20;
constexpr int NCH_MAX    = (kMaxT + C1 - 1) / C1;
constexpr int CH_BYTES   = CSTR / 5 * 32;

constexpr int P2_THREADS = 1024;
constexpr int NPG        = 2;
constexpr int GW         = 8;
constexpr int NPW        = NPG * GW;
constexpr int NCW        = 32 - NPW;
constexpr int PT         = GW * 32;
constexpr int RPT_RUN    = (NCH_MAX + PT - 1) / PT;
constexpr int RING_D     = 3;
constexpr int NBUF       = 2;
constexpr int BPB_MAX    = 13;
constexpr int P2_RPT     = (CAP + PT - 1) / PT;
static_assert(PT >= EB, "producer thread count");

__device__ __align__(128) unsigned char g_rec[(size_t)NCH_MAX * CH_BYTES];
__device__ __align__(128) uint16_t g_off[(size_t)NCH_MAX * OFF_STRIDE];

__device__ __forceinline__ int4 ld_stream4(const int4* p) { return __ldcs(p); }
__device__ __forceinline__ uint2 ld_stream2(const uint2* p) { return __ldcs(p); }

__device__ __forceinline__ float bf16r(float x) { return __bfloat162float(__float2bfloat16_rn(x)); }
__device__ __forceinline__ float bf16_bits_to_f(uint32_t h) { return __uint_as_float(h << 16); }
__device__ __forceinline__ uint32_t pack_bf16(float lo, float hi) {
    __nv_bfloat162 v = __floats2bfloat162_rn(lo, hi);
    return *reinterpret_cast<uint32_t*>(&v);
}

__device__ __noinline__ float cos_slow(float x) { return cosf(x); }
__device__ __forceinline__ float cos_acc(float x) {
    if (fabsf(x) > 1000.f) return cos_slow(x);
    float k = rintf(x * 0.15915494309189535f);
    float r = fmaf(k, -6.28318548202514648f, x);
    r = fmaf(k, 1.7484555314695172e-7f, r);
    return __cosf(r);
}
__device__ __forceinline__ float cbf_val(float freq, float ang) {
    return bf16r(cos_acc(bf16r(freq * ang)));
}
__device__ __noinline__ uint2 cbf3_slow(float x0, float x1, float x2) {
    return make_uint2(pack_bf16(cosf(x0), cosf(x1)), pack_bf16(cosf(x2), 0.f));
}
__device__ __forceinline__ uint2 cbf3(uint32_t abits, uint32_t f01, uint32_t f22, bool& big) {
    uint32_t a2 = abits | (abits << 16), p01, p22;
    asm("mul.rn.bf16x2 %0, %1, %2;" : "=r"(p01) : "r"(a2), "r"(f01));
    asm("mul.rn.bf16x2 %0, %1, %2;" : "=r"(p22) : "r"(a2), "r"(f22));
    float x0 = __uint_as_float(p01 << 16), x1 = __uint_as_float(p01 & 0xffff0000u), x2 = __uint_as_float(p22 << 16);
    big = !(fmaxf(fmaxf(fabsf(x0), fabsf(x1)), fabsf(x2)) <= 32.f);
    return make_uint2(pack_bf16(__cosf(x0), __cosf(x1)), pack_bf16(__cosf(x2), 0.f));
}
__device__ __forceinline__ uint2 cbf3_exact(uint32_t abits, uint32_t f01, uint32_t f22) {
    uint32_t a2 = abits | (abits << 16), p01, p22;
    asm("mul.rn.bf16x2 %0, %1, %2;" : "=r"(p01) : "r"(a2), "r"(f01));
    asm("mul.rn.bf16x2 %0, %1, %2;" : "=r"(p22) : "r"(a2), "r"(f22));
    return cbf3_slow(__uint_as_float(p01 << 16), __uint_as_float(p01 & 0xffff0000u), __uint_as_float(p22 << 16));
}
__device__ __forceinline__ void mma16816(float* d, uint32_t a0, uint32_t a1, uint32_t a2, uint32_t a3,
                                         uint32_t b0, uint32_t b1) {
    asm volatile("mma.sync.aligned.m16n8k16.row.col.f32.bf16.bf16.f32 {%0,%1,%2,%3}, {%4,%5,%6,%7}, {%8,%9}, {%0,%1,%2,%3};"
                 : "+f"(d[0]), "+f"(d[1]), "+f"(d[2]), "+f"(d[3])
                 : "r"(a0), "r"(a1), "r"(a2), "r"(a3), "r"(b0), "r"(b1));
}
__device__ __forceinline__ void mma1688(float* d, uint32_t a0, uint32_t a1, uint32_t b0) {
    asm volatile("mma.sync.aligned.m16n8k8.row.col.f32.bf16.bf16.f32 {%0,%1,%2,%3}, {%4,%5}, {%6}, {%0,%1,%2,%3};"
                 : "+f"(d[0]), "+f"(d[1]), "+f"(d[2]), "+f"(d[3])
                 : "r"(a0), "r"(a1), "r"(b0));
}

__device__ __forceinline__ uint32_t smem_u32(const void* p) { return (uint32_t)__cvta_generic_to_shared(p); }
__device__ __forceinline__ uint32_t lds32(uint32_t a) {
    uint32_t v; asm volatile("ld.shared.u32 %0, [%1];" : "=r"(v) : "r"(a) : "memory"); return v;
}

__global__ void __launch_bounds__(P1_THREADS, 1)
part_kernel(const int* __restrict__ idx_in, const int* __restrict__ idx_out,
            const uint16_t* __restrict__ angle, int T, int nchunks)
{
    extern __shared__ __align__(128) unsigned char smem1[];
    unsigned char* stage = smem1;
    int4* obuf = reinterpret_cast<int4*>(smem1 + CH_BYTES);
    uint32_t* s_cnt = reinterpret_cast<uint32_t*>(smem1 + CH_BYTES + P1_THREADS * P1_RPT * 4);
    __shared__ uint32_t s_warp[32];
    __shared__ __align__(8) uint64_t s_bar;

    const int tid = threadIdx.x;
    const uint32_t bar = (uint32_t)__cvta_generic_to_shared(&s_bar);
    if (tid == 0) {
        asm volatile("mbarrier.init.shared.b64 [%0], 1;" :: "r"(bar));
        asm volatile("fence.mbarrier_init.release.cluster;" ::: "memory");
    }
    __syncthreads();

    auto issue_o = [&](int chunk) {
        uint32_t bytes = (uint32_t)min(C1, T - chunk * C1) * 4u;
        asm volatile("mbarrier.arrive.expect_tx.shared.b64 _, [%0], %1;" :: "r"(bar), "r"(bytes) : "memory");
        asm volatile("cp.async.bulk.shared::cluster.global.mbarrier::complete_tx::bytes [%0], [%1], %2, [%3];"
                     :: "r"((uint32_t)__cvta_generic_to_shared(obuf)), "l"(idx_out + (size_t)chunk * C1), "r"(bytes), "r"(bar) : "memory");
    };
    int4 in[4];
    uint2 a[4];
    auto load_ia = [&](int chunk) {
#pragma unroll
        for (int j = 0; j < 4; j++) {
            int v = chunk * (C1 / 4) + j * P1_THREADS + tid;
            if (v * 4 < T) {
                in[j] = ld_stream4(reinterpret_cast<const int4*>(idx_in) + v);
                a[j]  = ld_stream2(reinterpret_cast<const uint2*>(angle) + v);
            }
        }
    };
    if (tid == 0) issue_o(blockIdx.x);
    load_ia(blockIdx.x);
    reinterpret_cast<uint2*>(s_cnt)[tid] = make_uint2(0, 0);
    __syncthreads();

    uint32_t phase = 0;
    for (int chunk = blockIdx.x; chunk < nchunks; chunk += gridDim.x) {
        const int nrec = min(C1, T - chunk * C1);
        {
            uint32_t done = 0;
            for (int spin = 0; !done && spin < (1 << 26); spin++)
                asm volatile("{ .reg .pred p; mbarrier.try_wait.parity.shared.b64 p, [%1], %2; selp.u32 %0, 1, 0, p; }"
                             : "=r"(done) : "r"(bar), "r"(phase) : "memory");
            phase ^= 1;
        }
        int4 o[4];
#pragma unroll
        for (int j = 0; j < 4; j++) {
            int v = j * P1_THREADS + tid;
            o[j] = (v * 4 < nrec) ? obuf[v] : make_int4(-1, -1, -1, -1);
        }
#pragma unroll
        for (int j = 0; j < 4; j++) {
            const int ov[4] = {o[j].x, o[j].y, o[j].z, o[j].w};
#pragma unroll
            for (int k = 0; k < 4; k++)
                if (ov[k] >= 0) atomicAdd(&s_cnt[(uint32_t)ov[k] >> EB_LOG], 1u);
        }
        __syncthreads();
        if (tid == 0 && chunk + (int)gridDim.x < nchunks) issue_o(chunk + gridDim.x);

        const uint2 c = reinterpret_cast<uint2*>(s_cnt)[tid];
        const uint32_t sum = c.x + c.y;
        uint32_t inc = sum;
#pragma unroll
        for (int d = 1; d < 32; d <<= 1) {
            uint32_t t = __shfl_up_sync(0xffffffffu, inc, d);
            if ((tid & 31) >= d) inc += t;
        }
        if ((tid & 31) == 31) s_warp[tid >> 5] = inc;
        __syncthreads();
        uint32_t wpre;
        {
            uint32_t x = s_warp[tid & 31];
#pragma unroll
            for (int d = 1; d < 32; d <<= 1) {
                uint32_t t = __shfl_up_sync(0xffffffffu, x, d);
                if ((tid & 31) >= d) x += t;
            }
            wpre = __shfl_sync(0xffffffffu, x, ((tid >> 5) + 31) & 31);
            if ((tid >> 5) == 0) wpre = 0;
        }
        const uint32_t ex = wpre + inc - sum;
        reinterpret_cast<uint2*>(s_cnt)[tid] = make_uint2(ex, ex + c.x);
        if (2 * tid < OFF_STRIDE)
            reinterpret_cast<uint32_t*>(g_off + (size_t)chunk * OFF_STRIDE)[tid] = ex | ((ex + c.x) << 16);
        if (tid == 0) asm volatile("cp.async.bulk.wait_group.read 0;" ::: "memory");
        __syncthreads();

#pragma unroll
        for (int j = 0; j < 4; j++) {
            const int ov[4] = {o[j].x, o[j].y, o[j].z, o[j].w};
            const int iv[4] = {in[j].x, in[j].y, in[j].z, in[j].w};
            const uint32_t av[4] = {a[j].x & 0xffffu, a[j].x >> 16, a[j].y & 0xffffu, a[j].y >> 16};
#pragma unroll
            for (int k = 0; k < 4; k++) {
                if (ov[k] >= 0) {
                    uint32_t p = atomicAdd(&s_cnt[(uint32_t)ov[k] >> EB_LOG], 1u);
                    const uint32_t sc = (p * 52429u) >> 18;
                    *reinterpret_cast<uint32_t*>(stage + 4 * p + 12 * sc) =
                        (uint32_t)iv[k] | ((uint32_t)(ov[k] & (EB - 1)) << IDX_BITS);
                    *reinterpret_cast<uint16_t*>(stage + 2 * p + 22 * sc + 20) = (uint16_t)av[k];
                }
            }
        }
        asm volatile("fence.proxy.async.shared::cta;" ::: "memory");
        if (chunk + (int)gridDim.x < nchunks) load_ia(chunk + gridDim.x);
        __syncthreads();
        reinterpret_cast<uint2*>(s_cnt)[tid] = make_uint2(0, 0);
        if (tid == 0) {
            uint32_t bytes = (uint32_t)((nrec + 4) / 5) * 32u;
            asm volatile("cp.async.bulk.global.shared::cta.bulk_group [%0], [%1], %2;"
                         :: "l"(g_rec + (size_t)chunk * CH_BYTES), "r"((uint32_t)__cvta_generic_to_shared(stage)), "r"(bytes) : "memory");
            asm volatile("cp.async.bulk.commit_group;" ::: "memory");
        }
        __syncthreads();
    }
    if (tid == 0) asm volatile("cp.async.bulk.wait_group 0;" ::: "memory");
}

constexpr int BUF_IDX   = 0;
constexpr int BUF_COS   = BUF_IDX + CAPP * 8;
constexpr int BUF_START = BUF_COS + CAPP * 2;
constexpr int BUF_BYTES = (BUF_START + (EB + 2) * 4 + 127) / 128 * 128;
constexpr int SM2_RING  = NBUF * BUF_BYTES;
constexpr int SM2_MAP   = SM2_RING + NCW * RING_D * 512;
constexpr int SMEM2     = SM2_MAP + NPG * CAP * 2;
static_assert(BUF_START >= EB * 46 * 4, "");

__device__ __forceinline__ void mbar_wait(uint32_t bar, uint32_t parity) {
    uint32_t done = 0;
#pragma unroll 1
    for (int spin = 0; spin < (1 << 24); spin++) {
        asm volatile("{ .reg .pred p; mbarrier.try_wait.parity.shared.b64 p, [%1], %2; selp.u32 %0, 1, 0, p; }"
                     : "=r"(done) : "r"(bar), "r"(parity) : "memory");
        if (done) break;
        __nanosleep(400);
    }
}
__device__ __forceinline__ void mbar_arrive(uint32_t bar) {
    asm volatile("mbarrier.arrive.shared.b64 _, [%0];" :: "r"(bar) : "memory");
}
__device__ __forceinline__ void group_sync(int grp) { asm volatile("bar.sync %0, %1;" :: "r"(grp + 1), "n"(PT) : "memory"); }

__global__ void __launch_bounds__(P2_THREADS, 1)
edge_kernel(const uint16_t* __restrict__ m, const int* __restrict__ idx_in, const int* __restrict__ idx_out,
            const uint16_t* __restrict__ dist, const uint16_t* __restrict__ angle,
            const uint16_t* __restrict__ centers, const uint16_t* __restrict__ ang_freq,
            const uint16_t* __restrict__ w_rbf, const uint16_t* __restrict__ w_sbf,
            const uint16_t* __restrict__ w_down, const uint16_t* __restrict__ w_up,
            uint16_t* __restrict__ out, int E, int T, int nchunks, int nb)
{
    extern __shared__ __align__(128) unsigned char smem2[];
    __shared__ __align__(16) uint16_t s_ro[NCH_MAX][BPB_MAX + 1];
    __shared__ uint32_t s_run_g[NPG][RPT_RUN * PT];
    __shared__ uint32_t s_hist_g[NPG][EB];
    __shared__ uint32_t s_ws_g[NPG][GW];
    __shared__ uint32_t s_nfix_g[NPG];
    __shared__ uint32_t s_wf[16][32];
    __shared__ float s_fc[4];
    __shared__ uint32_t s_fp[2];
    __shared__ uint32_t s_cen2[4];
    __shared__ uint32_t s_unit;
    __shared__ __align__(8) uint64_t s_bar[2 * NBUF];
    __shared__ float s_spill[NBUF * EB * 2];

    const int tid  = threadIdx.x;
    const int lane = tid & 31;
    const int warp = tid >> 5;
    const int b0 = (int)((long long)blockIdx.x * nb / gridDim.x);
    const int nbk = (int)((long long)(blockIdx.x + 1) * nb / gridDim.x) - b0;
    const uint32_t bar0 = smem_u32(s_bar);

    if (tid < 3) s_fc[tid] = bf16_bits_to_f(ang_freq[tid]);
    if (tid == 3) { s_fp[0] = (uint32_t)ang_freq[0] | ((uint32_t)ang_freq[1] << 16); s_fp[1] = (uint32_t)ang_freq[2] * 0x10001u; }
    if (tid >= 4 && tid < 8) s_cen2[tid - 4] = (uint32_t)centers[2 * (tid - 4)] | ((uint32_t)centers[2 * (tid - 4) + 1] << 16);
    if (tid == 8) {
        s_unit = 0;
        for (int i = 0; i < NPG; i++) s_nfix_g[i] = 0;
        for (int i = 0; i < NBUF; i++) {
            asm volatile("mbarrier.init.shared.b64 [%0], 1;" :: "r"(bar0 + i * 8));
            asm volatile("mbarrier.init.shared.b64 [%0], 16;" :: "r"(bar0 + (NBUF + i) * 8));
        }
    }
    {
        constexpr int NR = (NCH_MAX * 16 + P2_THREADS - 1) / P2_THREADS;
        uint16_t v[NR];
#pragma unroll
        for (int u = 0; u < NR; u++) {
            const int i = tid + u * P2_THREADS, c = i >> 4, j = i & 15;
            v[u] = (c < nchunks && j <= nbk) ? g_off[(size_t)c * OFF_STRIDE + b0 + j] : (uint16_t)0;
        }
#pragma unroll
        for (int u = 0; u < NR; u++) {
            const int i = tid + u * P2_THREADS, c = i >> 4, j = i & 15;
            if (c < nchunks && j <= nbk) s_ro[c][j] = v[u];
        }
    }
    if (tid < NPG * EB) (&s_hist_g[0][0])[tid] = 0;
    if (warp == 31) {
        const int g = lane >> 2, t = lane & 3;
        auto ld2 = [](const uint16_t* p0, const uint16_t* p1) -> uint32_t {
            return (uint32_t)__ldg(p0) | ((uint32_t)__ldg(p1) << 16);
        };
#pragma unroll
        for (int j = 0; j < 2; j++) {
            s_wf[0 + j][lane] = ld2(w_down + (2 * t + 0) * 16 + 8 * j + g, w_down + (2 * t + 1) * 16 + 8 * j + g);
            s_wf[2 + j][lane] = ld2(w_down + (2 * t + 8) * 16 + 8 * j + g, w_down + (2 * t + 9) * 16 + 8 * j + g);
#pragma unroll
            for (int l = 0; l < 3; l++)
                s_wf[4 + 2 * l + j][lane] = ld2(w_sbf + (3 * (2 * t) + l) * 16 + 8 * j + g, w_sbf + (3 * (2 * t + 1) + l) * 16 + 8 * j + g);
            const int col = 4 * (g >> 1) + 2 * j + (g & 1);
            s_wf[10 + j][lane] = ld2(w_up + (2 * t) * 16 + col, w_up + (2 * t + 1) * 16 + col);
            s_wf[12 + j][lane] = ld2(w_up + (2 * t + 8) * 16 + col, w_up + (2 * t + 9) * 16 + col);
            s_wf[14 + j][lane] = ld2(w_rbf + (2 * t) * 16 + col, w_rbf + (2 * t + 1) * 16 + col);
        }
    }
    __syncthreads();

    if (warp < NPW) {
        const int grp = warp / GW;
        const int gt = tid - grp * PT;
        const int gw = warp - grp * GW;
        uint16_t* s_map = reinterpret_cast<uint16_t*>(smem2 + SM2_MAP) + grp * CAP;
        uint32_t* s_run = s_run_g[grp];
        uint32_t* s_hist = s_hist_g[grp];
        uint32_t* s_ws = s_ws_g[grp];
        auto pscan = [&](uint32_t v, uint32_t& total) -> uint32_t {
            uint32_t inc = v;
#pragma unroll
            for (int d = 1; d < 32; d <<= 1) {
                uint32_t x = __shfl_up_sync(0xffffffffu, inc, d);
                if (lane >= d) inc += x;
            }
            if (lane == 31) s_ws[gw] = inc;
            group_sync(grp);
            uint32_t x = (lane < GW) ? s_ws[lane] : 0u;
#pragma unroll
            for (int d = 1; d < GW; d <<= 1) {
                uint32_t y = __shfl_up_sync(0xffffffffu, x, d);
                if (lane >= d) x += y;
            }
            total = __shfl_sync(0xffffffffu, x, GW - 1);
            uint32_t wp = __shfl_sync(0xffffffffu, x, (gw + 31) & 31);
            if (gw == 0) wp = 0;
            return wp + inc - v;
        };
#pragma unroll 1
        for (int k = grp; k < nbk; k += NPG) {
            const int kb = k % NBUF, kp = k / NBUF;
            unsigned char* buf = smem2 + kb * BUF_BYTES;
            uint2* s_idx = reinterpret_cast<uint2*>(buf + BUF_IDX);
            uint16_t* s_cos = reinterpret_cast<uint16_t*>(buf + BUF_COS);
            uint32_t* s_start = reinterpret_cast<uint32_t*>(buf + BUF_START);
            uint32_t n;
            {
                uint32_t st[RPT_RUN], len[RPT_RUN], sum = 0;
#pragma unroll
                for (int u = 0; u < RPT_RUN; u++) {
                    const int c = RPT_RUN * gt + u;
                    st[u] = 0; len[u] = 0;
                    if (c < nchunks) { st[u] = s_ro[c][k]; len[u] = (uint32_t)s_ro[c][k + 1] - st[u]; }
                    sum += len[u];
                }
                uint32_t pre = pscan(sum, n);
#pragma unroll
                for (int u = 0; u < RPT_RUN; u++) {
                    const int c = RPT_RUN * gt + u;
                    s_run[c] = c * CSTR + st[u] - pre;
                    if (n <= (uint32_t)CAP && len[u]) {
                        uint32_t j = pre;
                        const uint32_t je = pre + len[u];
                        if (j & 1u) s_map[j++] = (uint16_t)c;
                        for (; j + 1 < je; j += 2) *reinterpret_cast<uint32_t*>(s_map + j) = (uint32_t)c * 0x10001u;
                        if (j < je) s_map[j] = (uint16_t)c;
                    }
                    pre += len[u];
                }
            }
            group_sync(grp);
            const bool fast = n <= (uint32_t)CAP;
            uint32_t w[P2_RPT], av[P2_RPT];
            {
                const uint32_t nl = fast ? n : 0u;
#pragma unroll
                for (int r = 0; r < P2_RPT; r++) {
                    const uint32_t i = gt + r * PT;
                    w[r] = 0xffffffffu; av[r] = 0;
                    if (i < nl) {
                        const uint32_t P = s_run[s_map[i]] + i, h = __umulhi(P, 0xcccccccdu) >> 2;
                        w[r]  = __ldg(reinterpret_cast<const uint32_t*>(g_rec + (4 * P + 12 * h)));
                        av[r] = __ldg(reinterpret_cast<const uint16_t*>(g_rec + (2 * P + 22 * h + 20)));
                    }
                }
#pragma unroll
                for (int r = 0; r < P2_RPT; r++)
                    if (w[r] != 0xffffffffu) av[r] |= atomicAdd(&s_hist[w[r] >> IDX_BITS], 1u) << 16;
            }
            group_sync(grp);
            const uint32_t cnt1 = (gt < EB) ? s_hist[gt] : 0u;
            const uint32_t cnt = (cnt1 + 1u) & ~1u;
            uint32_t tot;
            const uint32_t ex = pscan(cnt, tot);
            if (k >= NBUF) mbar_wait(bar0 + (NBUF + kb) * 8, (kp - 1) & 1);
            if (gt < EB) {
                s_start[gt] = ex;
                s_hist[gt] = 0;
                if (gt == EB - 1) { s_start[EB] = tot; s_start[EB + 1] = fast ? 1u : 0u; }
                if (cnt != cnt1) {
                    const uint32_t pd = ex + cnt1;
                    s_idx[pd] = make_uint2(0xffffffffu, 0u);
                    s_cos[pd] = 0;
                }
            }
            group_sync(grp);
            if (fast) {
                const uint32_t f01 = s_fp[0], f22 = s_fp[1];
                bool anybig = false;
#pragma unroll
                for (int r = 0; r < P2_RPT; r++)
                    av[r] += s_start[(w[r] >> IDX_BITS) & (EB - 1)] << 16;
#pragma unroll
                for (int r = 0; r < P2_RPT; r++) {
                    bool big;
                    uint2 c = cbf3(av[r] & 0xffffu, f01, f22, big);
                    const uint32_t p = av[r] >> 16;
                    if (big) { c.x = av[r] & 0xffffu; c.y = 0xffffu; }
                    if (w[r] != 0xffffffffu) {
                        anybig |= big;
                        s_idx[p] = make_uint2((w[r] & ((1u << IDX_BITS) - 1)) * 32u, c.x);
                        s_cos[p] = (uint16_t)c.y;
                    }
                }
                if (anybig) s_nfix_g[grp] = 1;
                group_sync(grp);
                if (s_nfix_g[grp]) {
                    for (uint32_t p = gt; p < tot; p += PT) {
                        if (s_cos[p] == 0xffffu) {
                            const uint2 c = cbf3_exact(s_idx[p].y, s_fp[0], s_fp[1]);
                            s_idx[p].y = c.x;
                            s_cos[p] = (uint16_t)c.y;
                        }
                    }
                    group_sync(grp);
                    if (gt == 0) s_nfix_g[grp] = 0;
                    group_sync(grp);
                }
            } else {
                const float f0 = s_fc[0], f1 = s_fc[1], f2 = s_fc[2];
                float* sacc = reinterpret_cast<float*>(buf);
                float* spl = s_spill + kb * EB * 2;
                for (int i = gt; i < EB * 46; i += PT) sacc[i] = 0.f;
                for (int i = gt; i < EB * 2; i += PT) spl[i] = 0.f;
                group_sync(grp);
                const int b = b0 + k;
                for (int i = gt; i < T; i += PT) {
                    int o = idx_out[i];
                    if ((o >> EB_LOG) == b) {
                        float an = bf16_bits_to_f(angle[i]);
                        float c[3] = {cbf_val(f0, an), cbf_val(f1, an), cbf_val(f2, an)};
                        const uint16_t* row = m + (size_t)idx_in[i] * 16;
                        const int el = o & (EB - 1);
                        for (int kk = 0; kk < 48; kk++) {
                            float v = c[kk >> 4] * bf16_bits_to_f(row[kk & 15]);
                            atomicAdd(kk < 46 ? sacc + el * 46 + kk : spl + el * 2 + (kk - 46), v);
                        }
                    }
                }
                group_sync(grp);
            }
            if (gt == 0) mbar_arrive(bar0 + kb * 8);
        }
        return;
    }

    const int g = lane >> 2;
    const int t = lane & 3;
    const uint32_t sbase = smem_u32(smem2);
    const uint32_t dj = lane >> 1;
    const uint32_t lr = (lane & 7) + 8 * ((lane >> 3) & 1);
    const uint32_t ring_dst = sbase + SM2_RING + (warp - NPW) * (RING_D * 512) + (2 * dj + ((lane & 1) ^ ((dj >> 2) & 1))) * 16;
    const uint32_t ring_src = sbase + SM2_RING + (warp - NPW) * (RING_D * 512) + (2 * lr + ((uint32_t)(lane >> 4) ^ ((lr >> 2) & 1))) * 16;
    const char* msrc = reinterpret_cast<const char*>(m) + (lane & 1) * 16;

#pragma unroll 1
    while (true) {
        uint32_t unit = 0;
        if (lane == 0) unit = atomicAdd(&s_unit, 1u);
        unit = __shfl_sync(0xffffffffu, unit, 0);
        const int k = unit >> 4;
        if (k >= nbk) break;
        const int el = (unit & 15) * 16;
        const int kb = k % NBUF;
        const uint32_t bufa = sbase + kb * BUF_BYTES;
        const uint32_t sta = bufa + BUF_START + el * 4;
        mbar_wait(bar0 + kb * 8, (k / NBUF) & 1);

        float Tz[3][2][4];
        if (lds32(bufa + BUF_START + (EB + 1) * 4)) {
            const uint32_t p0 = lds32(sta), sB0 = lds32(sta + 32), sEnd = lds32(sta + 64);
            const int nA = (int)((sB0 - p0 + 15) >> 4);
            const int N  = (int)((sEnd - p0 + 15) >> 4);
            uint32_t ia = bufa + BUF_IDX + (p0 + dj) * 8;
            const uint32_t iae = bufa + BUF_IDX + sEnd * 8;
            uint32_t ioff = 0;
            uint32_t off = 0xffffffffu;
            if (ia < iae) off = lds32(ia);
            auto issue = [&]() {
                asm volatile("{ .reg .pred p; setp.eq.u32 p, %2, 0xffffffff;\n"
                             "  cp.async.cg.shared.global [%0], [%1], 16, p; }"
                             :: "r"(ring_dst + ioff), "l"(msrc + off), "r"(off) : "memory");
                asm volatile("cp.async.commit_group;" ::: "memory");
                ioff = (ioff == (RING_D - 1) * 512) ? 0 : ioff + 512;
                ia += 128;
                off = 0xffffffffu;
                if (ia < iae) off = lds32(ia);
            };
#pragma unroll
            for (int s0 = 0; s0 < RING_D - 1; s0++) issue();

            uint32_t coff = 0;
            uint32_t ca = (p0 + 2 * t) * 2;
            uint32_t b0r = 0, b1r = 0, b2r = 0, b3r = 0;
            float T0[2][4], T2[2][4];
            auto accum = [&](uint32_t d0, uint32_t len, uint32_t cadr) {
                uint32_t wa0 = 0, wa1 = 0, wb0 = 0, wb1 = 0, c20 = 0, c21 = 0;
                const uint32_t wadr = bufa + BUF_IDX + 4 + cadr * 4;
                if (d0 < len)     { wa0 = lds32(wadr);      wa1 = lds32(wadr + 8);  c20 = lds32(bufa + BUF_COS + cadr); }
                if (d0 + 8 < len) { wb0 = lds32(wadr + 64); wb1 = lds32(wadr + 72); c21 = lds32(bufa + BUF_COS + cadr + 16); }
                const uint32_t c00 = __byte_perm(wa0, wa1, 0x5410), c10 = __byte_perm(wa0, wa1, 0x7632);
                const uint32_t c01 = __byte_perm(wb0, wb1, 0x5410), c11 = __byte_perm(wb0, wb1, 0x7632);
                mma16816(T0[0], c00, c10, c01, c11, b0r, b1r);
                mma16816(T0[1], c00, c10, c01, c11, b2r, b3r);
                mma16816(T2[0], c20, 0u, c21, 0u, b0r, b1r);
                mma16816(T2[1], c20, 0u, c21, 0u, b2r, b3r);
            };
#pragma unroll 1
            for (int h = 0; h < 2; h++) {
                const uint32_t sg = lds32(sta + (8 * h + g) * 4);
                const uint32_t len = lds32(sta + (8 * h + g + 1) * 4) - sg;
                uint32_t d0 = p0 + 2 * t + (h ? 16 * nA : 0) - sg;
#pragma unroll
                for (int j = 0; j < 2; j++)
#pragma unroll
                    for (int i = 0; i < 4; i++) { T0[j][i] = 0.f; T2[j][i] = 0.f; }
                if (h && ((sB0 - p0) & 15u)) accum(d0 - 16, len, ca - 32);
#pragma unroll 1
                for (int n = h ? N - nA : nA; n > 0; n--) {
                    issue();
                    asm volatile("cp.async.wait_group %0;" :: "n"(RING_D - 1) : "memory");
                    __syncwarp();
                    asm volatile("ldmatrix.sync.aligned.m8n8.x4.trans.shared.b16 {%0,%1,%2,%3}, [%4];"
                                 : "=r"(b0r), "=r"(b1r), "=r"(b2r), "=r"(b3r) : "r"(ring_src + coff) : "memory");
                    coff = (coff == (RING_D - 1) * 512) ? 0 : coff + 512;
                    accum(d0, len, ca);
                    d0 += 16; ca += 32;
                }
                if (h == 0) {
#pragma unroll
                    for (int j = 0; j < 2; j++) {
#pragma unroll
                        for (int i = 0; i < 4; i++) Tz[0][j][i] = T0[j][i];
                        Tz[2][j][0] = T2[j][0]; Tz[2][j][1] = T2[j][1];
                    }
                } else {
#pragma unroll
                    for (int j = 0; j < 2; j++) {
#pragma unroll
                        for (int i = 0; i < 4; i++) Tz[1][j][i] = T0[j][i];
                        Tz[2][j][2] = T2[j][0]; Tz[2][j][3] = T2[j][1];
                    }
                }
            }
            asm volatile("cp.async.wait_group 0;" ::: "memory");
        } else {
            const float* sacc = reinterpret_cast<const float*>(smem2 + kb * BUF_BYTES);
            auto ga = [&](int e, int kk) -> float { return kk < 46 ? sacc[e * 46 + kk] : s_spill[kb * EB * 2 + e * 2 + kk - 46]; };
            const int ea = el + g, eb = ea + 8;
#pragma unroll
            for (int j = 0; j < 2; j++) {
                const int c = 8 * j + 2 * t;
                Tz[0][j][0] = ga(ea, c); Tz[0][j][1] = ga(ea, c + 1); Tz[0][j][2] = ga(ea, 16 + c); Tz[0][j][3] = ga(ea, 17 + c);
                Tz[1][j][0] = ga(eb, c); Tz[1][j][1] = ga(eb, c + 1); Tz[1][j][2] = ga(eb, 16 + c); Tz[1][j][3] = ga(eb, 17 + c);
                Tz[2][j][0] = ga(ea, 32 + c); Tz[2][j][1] = ga(ea, 33 + c); Tz[2][j][2] = ga(eb, 32 + c); Tz[2][j][3] = ga(eb, 33 + c);
            }
        }
        __syncwarp();
        if (lane == 0) mbar_arrive(bar0 + (NBUF + kb) * 8);

        const int eA = (b0 + k) * EB + el + g;
        const int eB = eA + 8;
        const bool okA = eA < E, okB = eB < E;
        uint2 mvA = make_uint2(0, 0), mvB = make_uint2(0, 0);
        if (okA) mvA = __ldg(reinterpret_cast<const uint2*>(m + (size_t)eA * 16 + 4 * t));
        if (okB) mvB = __ldg(reinterpret_cast<const uint2*>(m + (size_t)eB * 16 + 4 * t));

        const uint32_t cen2 = s_cen2[t];
        auto rbf2 = [&](uint32_t dbits) -> uint32_t {
            uint32_t d2 = dbits * 0x10001u, x, sq, ar;
            asm("sub.rn.bf16x2 %0, %1, %2;" : "=r"(x) : "r"(d2), "r"(cen2));
            asm("mul.rn.bf16x2 %0, %1, %1;" : "=r"(sq) : "r"(x));
            asm("mul.rn.bf16x2 %0, %1, %2;" : "=r"(ar) : "r"(sq), "r"(0xc120c120u));
            return pack_bf16(__expf(__uint_as_float(ar << 16)), __expf(__uint_as_float(ar & 0xffff0000u)));
        };
        const uint32_t ra0 = rbf2(okA ? (uint32_t)dist[eA] : 0u);
        const uint32_t ra1 = rbf2(okB ? (uint32_t)dist[eB] : 0u);

        float y[3][2][4];
#pragma unroll
        for (int tl = 0; tl < 3; tl++)
#pragma unroll
            for (int j = 0; j < 2; j++)
#pragma unroll
                for (int i = 0; i < 4; i++) y[tl][j][i] = 0.f;
        {
            uint32_t wd[2][2];
#pragma unroll
            for (int j = 0; j < 2; j++) { wd[j][0] = s_wf[0 + j][lane]; wd[j][1] = s_wf[2 + j][lane]; }
#pragma unroll
            for (int tl = 0; tl < 3; tl++) {
                const float* P = Tz[tl][0];
                const float* Q = Tz[tl][1];
                uint32_t h0 = pack_bf16(P[0], P[1]), h1 = pack_bf16(P[2], P[3]);
                uint32_t h2 = pack_bf16(Q[0], Q[1]), h3 = pack_bf16(Q[2], Q[3]);
#pragma unroll
                for (int j = 0; j < 2; j++) mma16816(y[tl][j], h0, h1, h2, h3, wd[j][0], wd[j][1]);
            }
        }
        float aggA[2][2] = {{0.f, 0.f}, {0.f, 0.f}}, aggB[2][2] = {{0.f, 0.f}, {0.f, 0.f}};
#pragma unroll
        for (int l = 0; l < 3; l++) {
#pragma unroll
            for (int j = 0; j < 2; j++) {
                float G[4] = {0.f, 0.f, 0.f, 0.f};
                mma1688(G, ra0, ra1, s_wf[4 + 2 * l + j][lane]);
                float ya0, ya1, yb0, yb1;
                if (l == 0)      { ya0 = y[0][j][0]; ya1 = y[0][j][1]; yb0 = y[1][j][0]; yb1 = y[1][j][1]; }
                else if (l == 1) { ya0 = y[0][j][2]; ya1 = y[0][j][3]; yb0 = y[1][j][2]; yb1 = y[1][j][3]; }
                else             { ya0 = y[2][j][0]; ya1 = y[2][j][1]; yb0 = y[2][j][2]; yb1 = y[2][j][3]; }
                aggA[j][0] = fmaf(ya0, G[0], aggA[j][0]); aggA[j][1] = fmaf(ya1, G[1], aggA[j][1]);
                aggB[j][0] = fmaf(yb0, G[2], aggB[j][0]); aggB[j][1] = fmaf(yb1, G[3], aggB[j][1]);
            }
        }
        float u[2][4], rw[2][4];
        {
            uint32_t h0 = pack_bf16(aggA[0][0], aggA[0][1]), h1 = pack_bf16(aggB[0][0], aggB[0][1]);
            uint32_t h2 = pack_bf16(aggA[1][0], aggA[1][1]), h3 = pack_bf16(aggB[1][0], aggB[1][1]);
#pragma unroll
            for (int j = 0; j < 2; j++) {
#pragma unroll
                for (int i = 0; i < 4; i++) { u[j][i] = 0.f; rw[j][i] = 0.f; }
                mma16816(u[j], h0, h1, h2, h3, s_wf[10 + j][lane], s_wf[12 + j][lane]);
                mma1688(rw[j], ra0, ra1, s_wf[14 + j][lane]);
            }
        }
        if (okA) {
            float o0 = fmaf(u[0][0], rw[0][0], __uint_as_float(mvA.x << 16));
            float o1 = fmaf(u[0][1], rw[0][1], __uint_as_float(mvA.x & 0xffff0000u));
            float o2 = fmaf(u[1][0], rw[1][0], __uint_as_float(mvA.y << 16));
            float o3 = fmaf(u[1][1], rw[1][1], __uint_as_float(mvA.y & 0xffff0000u));
            *reinterpret_cast<uint2*>(out + (size_t)eA * 16 + 4 * t) = make_uint2(pack_bf16(o0, o1), pack_bf16(o2, o3));
        }
        if (okB) {
            float o0 = fmaf(u[0][2], rw[0][2], __uint_as_float(mvB.x << 16));
            float o1 = fmaf(u[0][3], rw[0][3], __uint_as_float(mvB.x & 0xffff0000u));
            float o2 = fmaf(u[1][2], rw[1][2], __uint_as_float(mvB.y << 16));
            float o3 = fmaf(u[1][3], rw[1][3], __uint_as_float(mvB.y & 0xffff0000u));
            *reinterpret_cast<uint2*>(out + (size_t)eB * 16 + 4 * t) = make_uint2(pack_bf16(o0, o1), pack_bf16(o2, o3));
        }
    }
}

}

extern "C" void kernel_launch(void* const* d_in, const int* in_sizes, int n_in,
                              void* d_out, int out_size) {
    const uint16_t* m        = (const uint16_t*)d_in[0];
    const int*      idx_in   = (const int*)d_in[1];
    const int*      idx_out  = (const int*)d_in[2];
    const uint16_t* dist     = (const uint16_t*)d_in[3];
    const uint16_t* angle    = (const uint16_t*)d_in[4];
    const uint16_t* centers  = (const uint16_t*)d_in[5];
    const uint16_t* ang_freq = (const uint16_t*)d_in[6];
    const uint16_t* w_rbf    = (const uint16_t*)d_in[7];
    const uint16_t* w_sbf    = (const uint16_t*)d_in[8];
    const uint16_t* w_down   = (const uint16_t*)d_in[9];
    const uint16_t* w_up     = (const uint16_t*)d_in[10];
    uint16_t* out = (uint16_t*)d_out;
    const int E = in_sizes[3];
    const int T = in_sizes[1];

    constexpr int SMEM1 = CH_BYTES + P1_THREADS * P1_RPT * 4 + NB_PAD * 4;
    static int num_sms = 0;
    if (!num_sms) {
        cudaFuncSetAttribute(part_kernel, cudaFuncAttributeMaxDynamicSharedMemorySize, SMEM1);
        cudaFuncSetAttribute(edge_kernel, cudaFuncAttributeMaxDynamicSharedMemorySize, SMEM2);
        int dev = 0;
        cudaGetDevice(&dev);
        cudaDeviceGetAttribute(&num_sms, cudaDevAttrMultiProcessorCount, dev);
        if (num_sms <= 0) num_sms = 132;
    }
    const int nb = (E + EB - 1) / EB;
    const int nchunks = (T + C1 - 1) / C1;
    const int grid2 = max(min(num_sms, nb), (nb + BPB_MAX - 2) / (BPB_MAX - 1));
    part_kernel<<<min(nchunks, num_sms), P1_THREADS, SMEM1>>>(idx_in, idx_out, angle, T, nchunks);
    edge_kernel<<<grid2, P2_THREADS, SMEM2>>>(m, idx_in, idx_out, dist, angle, centers, ang_freq,
                                              w_rbf, w_sbf, w_down, w_up, out, E, T, nchunks, nb);
}
```
